```python
import torch

def _softmax(x, axis=-1):
    return torch.softmax(x, dim=axis)
def _gelu(x):
    return torch.nn.functional.gelu(x, approximate="tanh")
def _silu(x):
    return torch.nn.functional.silu(x)
def _sigmoid(x):
    return torch.sigmoid(x)
def _layernorm(x, axis=-1, eps=1e-5):
    m = x.mean(dim=axis, keepdim=True)
    v = x.var(dim=axis, keepdim=True, unbiased=False)
    return (x - m) / torch.sqrt(v + eps)
def _scatter_add(tgt, idx, src, axis=0):
    return tgt.clone().index_add_(axis, idx, src)
def _segment_sum(src, seg, n):
    out = torch.zeros((n,) + src.shape[1:], dtype=src.dtype)
    return out.index_add_(0, seg, src)
def _pad(x, pw):
    flat = tuple(v for pair in reversed(pw) for v in pair)
    return torch.nn.functional.pad(x, flat)

kernel_name = 'parallel_sum__compressed_kv_cla__mixer_token_mlp__prompt'

def setup_inputs():

    _w = (lambda a: (lambda t: t.to(torch.bfloat16) if t.is_floating_point() else t)(torch.as_tensor(a)))
    def _A_setup():
        B, H, Sq, Sk, D, M = 1, 32, 2048, 2048, 128, 640
        Dc = 4 * D
        return {
            "x": _w((lambda *s: torch.randn(*s, dtype=torch.bfloat16) * 0.05)(B, Sq, M)),
            "c_kv": _w((lambda *s: torch.randn(*s, dtype=torch.bfloat16) * 0.2)(B, Sk, Dc)),
            "w_q": _w((lambda *s: torch.randn(*s, dtype=torch.bfloat16) * 6.4)(M, H, D) * (M ** -0.5)),
            "w_uk": _w((lambda *s: torch.randn(*s, dtype=torch.bfloat16) * 6.4)(Dc, H, D) * (Dc ** -0.5)),
            "w_uv": _w((lambda *s: torch.randn(*s, dtype=torch.bfloat16) * 0.2)(Dc, H, D) * (Dc ** -0.5)),
            "w_o": _w((lambda *s: torch.randn(*s, dtype=torch.bfloat16) * 0.2)(H, D, M) * ((H * D) ** -0.5)),
        }
    _A_in = _A_setup()

    def _B_setup():
        B, S, D, F = 1, 2048, 640, 1728
        return {
            "x": _w((lambda *s: torch.randn(*s, dtype=torch.bfloat16) * 0.05)(B, S, D)),
            "w1": _w((lambda *s: torch.randn(*s, dtype=torch.bfloat16) * 0.4)(S, F) * (S ** -0.5)),
            "b1": _w((lambda *s: torch.randn(*s, dtype=torch.bfloat16) * 3.2)(F) * 0.02),
            "w2": _w((lambda *s: torch.randn(*s, dtype=torch.bfloat16) * 0.2)(F, S) * (F ** -0.5)),
            "b2": _w((lambda *s: torch.randn(*s, dtype=torch.bfloat16) * 0.8)(S) * 0.02),
        }
    _B_in = _B_setup()

    return {
        "A_x": _A_in["x"],
        "A_c_kv": _A_in["c_kv"],
        "A_w_q": _A_in["w_q"],
        "A_w_uk": _A_in["w_uk"],
        "A_w_uv": _A_in["w_uv"],
        "A_w_o": _A_in["w_o"],
        "B_x": _B_in["x"],
        "B_w1": _B_in["w1"],
        "B_b1": _B_in["b1"],
        "B_w2": _B_in["w2"],
        "B_b2": _B_in["b2"],
    }

def reference(A_x, A_c_kv, A_w_q, A_w_uk, A_w_uv, A_w_o, B_x, B_w1, B_b1, B_w2, B_b2):
    def _A_ref(x, c_kv, w_q, w_uk, w_uv, w_o):
        B, Sq, M = x.shape[0], x.shape[1], x.shape[2]
        Sk = c_kv.shape[1]
        H, D = w_q.shape[1], w_q.shape[2]
        q = torch.einsum("bqm,mhd->bhqd", x, w_q)
        k = torch.einsum("bkc,chd->bhkd", c_kv, w_uk)
        v = torch.einsum("bkc,chd->bhkd", c_kv, w_uv)
        scores = torch.einsum("bhqd,bhkd->bhqk", q, k) * (D ** -0.5)
        off = Sk - Sq
        qi = torch.arange(Sq)[:, None]
        kj = torch.arange(Sk)[None, :]
        cmask = kj <= (qi + off)
        scores = torch.where(cmask[None, None], scores, -1e9)
        p = _softmax(scores, axis=-1)
        ctx = torch.einsum("bhqk,bhkd->bhqd", p, v)
        return torch.einsum("bhqd,hdm->bqm", ctx, w_o)

    def _B_ref(x, w1, b1, w2, b2):
        B, S, D = x.shape
        h = _layernorm(x, axis=-1)
        u = torch.einsum("bsd,sf->bdf", h, w1) + b1
        u = _gelu(u)
        y = torch.einsum("bdf,fs->bds", u, w2) + b2
        return (lambda x, *d: x.permute(*d))(y, 0, 2, 1)

    x = A_x
    xn = _layernorm(x, axis=-1)
    return x + _A_ref(xn, A_c_kv, A_w_q, A_w_uk, A_w_uv, A_w_o) + _B_ref(xn, B_w1, B_b1, B_w2, B_b2)
```

```cpp
#include <cuda_runtime.h>
#include <cuda_bf16.h>
#include <cuda.h>
#include <stdint.h>

typedef __nv_bfloat16 bf16;

constexpr int SEQ = 2048;
constexpr int DM  = 640;
constexpr int DC  = 512;
constexpr int NH  = 32;
constexpr int HD  = 128;
constexpr int FF  = 1728;

__device__ __align__(1024) bf16  g_xn[SEQ * DM];
__device__ __align__(1024) bf16  g_h[SEQ * DM];
__device__ __align__(1024) bf16  g_kv[64 * SEQ * HD];
__device__ __align__(1024) bf16  g_ctx[SEQ * NH * HD];
__device__ __align__(1024) bf16  g_uT[FF * DM];
__device__ __align__(1024) float g_acc[SEQ * DM];
__device__ int g_abort = 0;

__device__ __forceinline__ uint32_t smem_u32(const void* p) { return (uint32_t)__cvta_generic_to_shared(p); }
__device__ __forceinline__ void mbar_init(uint32_t bar, uint32_t count) {
    asm volatile("mbarrier.init.shared::cta.b64 [%0], %1;" :: "r"(bar), "r"(count) : "memory");
}
__device__ __forceinline__ void mbar_expect_tx(uint32_t bar, uint32_t bytes) {
    asm volatile("mbarrier.arrive.expect_tx.shared::cta.b64 _, [%0], %1;" :: "r"(bar), "r"(bytes) : "memory");
}
__device__ __forceinline__ void mbar_arrive(uint32_t bar) {
    asm volatile("mbarrier.arrive.shared::cta.b64 _, [%0];" :: "r"(bar) : "memory");
}
__device__ __forceinline__ void mbar_arrive_cluster(uint32_t bar_cluster_addr) {
    asm volatile("mbarrier.arrive.shared::cluster.b64 _, [%0];" :: "r"(bar_cluster_addr) : "memory");
}
__device__ __forceinline__ bool mbar_try_wait(uint32_t bar, uint32_t parity) {
    uint32_t ok;
    asm volatile("{\n.reg .pred p;\nmbarrier.try_wait.parity.shared::cta.b64 p, [%1], %2;\nselp.u32 %0, 1, 0, p;\n}\n"
                 : "=r"(ok) : "r"(bar), "r"(parity) : "memory");
    return ok != 0;
}
__device__ __forceinline__ void mbar_wait(uint32_t bar, uint32_t parity) {
    if (mbar_try_wait(bar, parity)) return;
    uint32_t spins = 0;
    while (!mbar_try_wait(bar, parity)) {
        if (++spins > (1u << 24)) __trap();
    }
}
__device__ __forceinline__ uint32_t mapa_u32(uint32_t addr, uint32_t rank) {
    uint32_t r;
    asm volatile("mapa.shared::cluster.u32 %0, %1, %2;" : "=r"(r) : "r"(addr), "r"(rank));
    return r;
}
__device__ __forceinline__ uint32_t cluster_rank() {
    uint32_t r;
    asm volatile("mov.u32 %0, %%cluster_ctarank;" : "=r"(r));
    return r;
}
__device__ __forceinline__ void cluster_sync_all() {
    asm volatile("barrier.cluster.arrive.release.aligned;\nbarrier.cluster.wait.acquire.aligned;" ::: "memory");
}
__device__ __forceinline__ void tma_load(uint32_t dst, const CUtensorMap* map, int c0, int c1, uint32_t bar) {
    asm volatile("cp.async.bulk.tensor.2d.shared::cluster.global.mbarrier::complete_tx::bytes [%0], [%1, {%3, %4}], [%2];"
                 :: "r"(dst), "l"((uint64_t)map), "r"(bar), "r"(c0), "r"(c1) : "memory");
}
__device__ __forceinline__ void tma_load_mc(uint32_t dst, const CUtensorMap* map, int c0, int c1, uint32_t bar) {
    asm volatile("cp.async.bulk.tensor.2d.shared::cluster.global.mbarrier::complete_tx::bytes.multicast::cluster [%0], [%1, {%3, %4}], [%2], %5;"
                 :: "r"(dst), "l"((uint64_t)map), "r"(bar), "r"(c0), "r"(c1), "h"((uint16_t)3) : "memory");
}
__device__ __forceinline__ void tma_store(const CUtensorMap* map, uint32_t src, int c0, int c1) {
    asm volatile("cp.async.bulk.tensor.2d.global.shared::cta.bulk_group [%0, {%2, %3}], [%1];"
                 :: "l"((uint64_t)map), "r"(src), "r"(c0), "r"(c1) : "memory");
}
__device__ __forceinline__ void bulk_commit() { asm volatile("cp.async.bulk.commit_group;" ::: "memory"); }
template<int N> __device__ __forceinline__ void bulk_wait_read() { asm volatile("cp.async.bulk.wait_group.read %0;" :: "n"(N) : "memory"); }
template<int N> __device__ __forceinline__ void bulk_wait() { asm volatile("cp.async.bulk.wait_group %0;" :: "n"(N) : "memory"); }
__device__ __forceinline__ void fence_async_smem() { asm volatile("fence.proxy.async.shared::cta;" ::: "memory"); }
__device__ __forceinline__ void prefetch_tmap(const CUtensorMap* map) {
    asm volatile("prefetch.tensormap [%0];" :: "l"((uint64_t)map) : "memory");
}
__device__ __forceinline__ void named_bar_sync(int id, int n) { asm volatile("bar.sync %0, %1;" :: "r"(id), "r"(n) : "memory"); }
__device__ __forceinline__ void named_bar_arrive(int id, int n) { asm volatile("bar.arrive %0, %1;" :: "r"(id), "r"(n) : "memory"); }

__device__ __forceinline__ void ldmatrix_x4(uint32_t& r0, uint32_t& r1, uint32_t& r2, uint32_t& r3, uint32_t addr) {
    asm volatile("ldmatrix.sync.aligned.m8n8.x4.shared.b16 {%0, %1, %2, %3}, [%4];"
                 : "=r"(r0), "=r"(r1), "=r"(r2), "=r"(r3) : "r"(addr) : "memory");
}
__device__ __forceinline__ void stmatrix_x4(uint32_t addr, uint32_t r0, uint32_t r1, uint32_t r2, uint32_t r3) {
    asm volatile("stmatrix.sync.aligned.m8n8.x4.shared.b16 [%0], {%1, %2, %3, %4};"
                 :: "r"(addr), "r"(r0), "r"(r1), "r"(r2), "r"(r3) : "memory");
}
__device__ __forceinline__ uint32_t pack_bf16(float lo, float hi) {
    uint32_t r;
    asm("cvt.rn.bf16x2.f32 %0, %1, %2;" : "=r"(r) : "f"(hi), "f"(lo));
    return r;
}
__device__ __forceinline__ float ex2(float x) {
    float y;
    asm("ex2.approx.ftz.f32 %0, %1;" : "=f"(y) : "f"(x));
    return y;
}
__device__ __forceinline__ float bf16r(float x) { return __bfloat162float(__float2bfloat16_rn(x)); }

#define PROF_STAMP(ph, i)
#define PROF_ITER(slot, i)
__device__ __forceinline__ uint64_t make_desc(uint32_t addr, uint32_t lbo, uint32_t sbo) {
    return (uint64_t)((addr & 0x3FFFF) >> 4) | ((uint64_t)(lbo >> 4) << 16) | ((uint64_t)(sbo >> 4) << 32) | (1ull << 62);
}
__device__ __forceinline__ void wg_fence() { asm volatile("wgmma.fence.sync.aligned;" ::: "memory"); }
__device__ __forceinline__ void wg_commit() { asm volatile("wgmma.commit_group.sync.aligned;" ::: "memory"); }
template<int N> __device__ __forceinline__ void wg_wait() { asm volatile("wgmma.wait_group.sync.aligned %0;" :: "n"(N) : "memory"); }
template<int R> __device__ __forceinline__ void reg_alloc() { asm volatile("setmaxnreg.inc.sync.aligned.u32 %0;" :: "n"(R)); }
template<int R> __device__ __forceinline__ void reg_dealloc() { asm volatile("setmaxnreg.dec.sync.aligned.u32 %0;" :: "n"(R)); }
template<int N> __device__ __forceinline__ void fence_regs(float (&d)[N]) {
#pragma unroll
    for (int i = 0; i < N; i++) asm volatile("" : "+f"(d[i]) :: "memory");
}
template<int N> __device__ __forceinline__ void fence_regs_u(uint32_t (&d)[N]) {
#pragma unroll
    for (int i = 0; i < N; i++) asm volatile("" : "+r"(d[i]) :: "memory");
}

template<int TB>
__device__ __forceinline__ void wgmma_m64n8k16_rs(float (&d)[4], uint32_t a0, uint32_t a1, uint32_t a2, uint32_t a3, uint64_t db, int scale_d) {
    asm volatile("{\n.reg .pred p;\n"
        "setp.ne.b32 p, %9, 0;\n"
        "wgmma.mma_async.sync.aligned.m64n8k16.f32.bf16.bf16 "
        "{%0, %1, %2, %3}, "
        "{%4, %5, %6, %7}, %8, p, 1, 1, %10;\n}\n"
        : "+f"(d[0]), "+f"(d[1]), "+f"(d[2]), "+f"(d[3])
        : "r"(a0), "r"(a1), "r"(a2), "r"(a3), "l"(db), "r"(scale_d), "n"(TB));
}
template<int TB>
__device__ __forceinline__ void wgmma_m64n64k16_rs(float (&d)[32], uint32_t a0, uint32_t a1, uint32_t a2, uint32_t a3, uint64_t db, int scale_d) {
    asm volatile("{\n.reg .pred p;\n"
        "setp.ne.b32 p, %37, 0;\n"
        "wgmma.mma_async.sync.aligned.m64n64k16.f32.bf16.bf16 "
        "{%0, %1, %2, %3, %4, %5, %6, %7, %8, %9, %10, %11, %12, %13, %14, %15, %16, %17, %18, %19, %20, %21, %22, %23, %24, %25, %26, %27, %28, %29, %30, %31}, "
        "{%32, %33, %34, %35}, %36, p, 1, 1, %38;\n}\n"
        : "+f"(d[0]), "+f"(d[1]), "+f"(d[2]), "+f"(d[3]), "+f"(d[4]), "+f"(d[5]), "+f"(d[6]), "+f"(d[7]), "+f"(d[8]), "+f"(d[9]), "+f"(d[10]), "+f"(d[11]), "+f"(d[12]), "+f"(d[13]), "+f"(d[14]), "+f"(d[15]), "+f"(d[16]), "+f"(d[17]), "+f"(d[18]), "+f"(d[19]), "+f"(d[20]), "+f"(d[21]), "+f"(d[22]), "+f"(d[23]), "+f"(d[24]), "+f"(d[25]), "+f"(d[26]), "+f"(d[27]), "+f"(d[28]), "+f"(d[29]), "+f"(d[30]), "+f"(d[31])
        : "r"(a0), "r"(a1), "r"(a2), "r"(a3), "l"(db), "r"(scale_d), "n"(TB));
}
template<int TB>
__device__ __forceinline__ void wgmma_m64n128k16_rs(float (&d)[64], uint32_t a0, uint32_t a1, uint32_t a2, uint32_t a3, uint64_t db, int scale_d) {
    asm volatile("{\n.reg .pred p;\n"
        "setp.ne.b32 p, %69, 0;\n"
        "wgmma.mma_async.sync.aligned.m64n128k16.f32.bf16.bf16 "
        "{%0, %1, %2, %3, %4, %5, %6, %7, %8, %9, %10, %11, %12, %13, %14, %15, %16, %17, %18, %19, %20, %21, %22, %23, %24, %25, %26, %27, %28, %29, %30, %31, %32, %33, %34, %35, %36, %37, %38, %39, %40, %41, %42, %43, %44, %45, %46, %47, %48, %49, %50, %51, %52, %53, %54, %55, %56, %57, %58, %59, %60, %61, %62, %63}, "
        "{%64, %65, %66, %67}, %68, p, 1, 1, %70;\n}\n"
        : "+f"(d[0]), "+f"(d[1]), "+f"(d[2]), "+f"(d[3]), "+f"(d[4]), "+f"(d[5]), "+f"(d[6]), "+f"(d[7]), "+f"(d[8]), "+f"(d[9]), "+f"(d[10]), "+f"(d[11]), "+f"(d[12]), "+f"(d[13]), "+f"(d[14]), "+f"(d[15]), "+f"(d[16]), "+f"(d[17]), "+f"(d[18]), "+f"(d[19]), "+f"(d[20]), "+f"(d[21]), "+f"(d[22]), "+f"(d[23]), "+f"(d[24]), "+f"(d[25]), "+f"(d[26]), "+f"(d[27]), "+f"(d[28]), "+f"(d[29]), "+f"(d[30]), "+f"(d[31]), "+f"(d[32]), "+f"(d[33]), "+f"(d[34]), "+f"(d[35]), "+f"(d[36]), "+f"(d[37]), "+f"(d[38]), "+f"(d[39]), "+f"(d[40]), "+f"(d[41]), "+f"(d[42]), "+f"(d[43]), "+f"(d[44]), "+f"(d[45]), "+f"(d[46]), "+f"(d[47]), "+f"(d[48]), "+f"(d[49]), "+f"(d[50]), "+f"(d[51]), "+f"(d[52]), "+f"(d[53]), "+f"(d[54]), "+f"(d[55]), "+f"(d[56]), "+f"(d[57]), "+f"(d[58]), "+f"(d[59]), "+f"(d[60]), "+f"(d[61]), "+f"(d[62]), "+f"(d[63])
        : "r"(a0), "r"(a1), "r"(a2), "r"(a3), "l"(db), "r"(scale_d), "n"(TB));
}
template<int TA, int TB>
__device__ __forceinline__ void wgmma_m64n128k16_ss(float (&d)[64], uint64_t da, uint64_t db, int scale_d) {
    asm volatile("{\n.reg .pred p;\n"
        "setp.ne.b32 p, %66, 0;\n"
        "wgmma.mma_async.sync.aligned.m64n128k16.f32.bf16.bf16 "
        "{%0, %1, %2, %3, %4, %5, %6, %7, %8, %9, %10, %11, %12, %13, %14, %15, %16, %17, %18, %19, %20, %21, %22, %23, %24, %25, %26, %27, %28, %29, %30, %31, %32, %33, %34, %35, %36, %37, %38, %39, %40, %41, %42, %43, %44, %45, %46, %47, %48, %49, %50, %51, %52, %53, %54, %55, %56, %57, %58, %59, %60, %61, %62, %63}, "
        "%64, %65, p, 1, 1, %67, %68;\n}\n"
        : "+f"(d[0]), "+f"(d[1]), "+f"(d[2]), "+f"(d[3]), "+f"(d[4]), "+f"(d[5]), "+f"(d[6]), "+f"(d[7]), "+f"(d[8]), "+f"(d[9]), "+f"(d[10]), "+f"(d[11]), "+f"(d[12]), "+f"(d[13]), "+f"(d[14]), "+f"(d[15]), "+f"(d[16]), "+f"(d[17]), "+f"(d[18]), "+f"(d[19]), "+f"(d[20]), "+f"(d[21]), "+f"(d[22]), "+f"(d[23]), "+f"(d[24]), "+f"(d[25]), "+f"(d[26]), "+f"(d[27]), "+f"(d[28]), "+f"(d[29]), "+f"(d[30]), "+f"(d[31]), "+f"(d[32]), "+f"(d[33]), "+f"(d[34]), "+f"(d[35]), "+f"(d[36]), "+f"(d[37]), "+f"(d[38]), "+f"(d[39]), "+f"(d[40]), "+f"(d[41]), "+f"(d[42]), "+f"(d[43]), "+f"(d[44]), "+f"(d[45]), "+f"(d[46]), "+f"(d[47]), "+f"(d[48]), "+f"(d[49]), "+f"(d[50]), "+f"(d[51]), "+f"(d[52]), "+f"(d[53]), "+f"(d[54]), "+f"(d[55]), "+f"(d[56]), "+f"(d[57]), "+f"(d[58]), "+f"(d[59]), "+f"(d[60]), "+f"(d[61]), "+f"(d[62]), "+f"(d[63])
        : "l"(da), "l"(db), "r"(scale_d), "n"(TA), "n"(TB));
}
template<int TA, int TB>
__device__ __forceinline__ void wgmma_m64n192k16_ss(float (&d)[96], uint64_t da, uint64_t db, int scale_d) {
    asm volatile("{\n.reg .pred p;\n"
        "setp.ne.b32 p, %98, 0;\n"
        "wgmma.mma_async.sync.aligned.m64n192k16.f32.bf16.bf16 "
        "{%0, %1, %2, %3, %4, %5, %6, %7, %8, %9, %10, %11, %12, %13, %14, %15, %16, %17, %18, %19, %20, %21, %22, %23, %24, %25, %26, %27, %28, %29, %30, %31, %32, %33, %34, %35, %36, %37, %38, %39, %40, %41, %42, %43, %44, %45, %46, %47, %48, %49, %50, %51, %52, %53, %54, %55, %56, %57, %58, %59, %60, %61, %62, %63, %64, %65, %66, %67, %68, %69, %70, %71, %72, %73, %74, %75, %76, %77, %78, %79, %80, %81, %82, %83, %84, %85, %86, %87, %88, %89, %90, %91, %92, %93, %94, %95}, "
        "%96, %97, p, 1, 1, %99, %100;\n}\n"
        : "+f"(d[0]), "+f"(d[1]), "+f"(d[2]), "+f"(d[3]), "+f"(d[4]), "+f"(d[5]), "+f"(d[6]), "+f"(d[7]), "+f"(d[8]), "+f"(d[9]), "+f"(d[10]), "+f"(d[11]), "+f"(d[12]), "+f"(d[13]), "+f"(d[14]), "+f"(d[15]), "+f"(d[16]), "+f"(d[17]), "+f"(d[18]), "+f"(d[19]), "+f"(d[20]), "+f"(d[21]), "+f"(d[22]), "+f"(d[23]), "+f"(d[24]), "+f"(d[25]), "+f"(d[26]), "+f"(d[27]), "+f"(d[28]), "+f"(d[29]), "+f"(d[30]), "+f"(d[31]), "+f"(d[32]), "+f"(d[33]), "+f"(d[34]), "+f"(d[35]), "+f"(d[36]), "+f"(d[37]), "+f"(d[38]), "+f"(d[39]), "+f"(d[40]), "+f"(d[41]), "+f"(d[42]), "+f"(d[43]), "+f"(d[44]), "+f"(d[45]), "+f"(d[46]), "+f"(d[47]), "+f"(d[48]), "+f"(d[49]), "+f"(d[50]), "+f"(d[51]), "+f"(d[52]), "+f"(d[53]), "+f"(d[54]), "+f"(d[55]), "+f"(d[56]), "+f"(d[57]), "+f"(d[58]), "+f"(d[59]), "+f"(d[60]), "+f"(d[61]), "+f"(d[62]), "+f"(d[63]), "+f"(d[64]), "+f"(d[65]), "+f"(d[66]), "+f"(d[67]), "+f"(d[68]), "+f"(d[69]), "+f"(d[70]), "+f"(d[71]), "+f"(d[72]), "+f"(d[73]), "+f"(d[74]), "+f"(d[75]), "+f"(d[76]), "+f"(d[77]), "+f"(d[78]), "+f"(d[79]), "+f"(d[80]), "+f"(d[81]), "+f"(d[82]), "+f"(d[83]), "+f"(d[84]), "+f"(d[85]), "+f"(d[86]), "+f"(d[87]), "+f"(d[88]), "+f"(d[89]), "+f"(d[90]), "+f"(d[91]), "+f"(d[92]), "+f"(d[93]), "+f"(d[94]), "+f"(d[95])
        : "l"(da), "l"(db), "r"(scale_d), "n"(TA), "n"(TB));
}
template<int TA, int TB>
__device__ __forceinline__ void wgmma_m64n256k16_ss(float (&d)[128], uint64_t da, uint64_t db, int scale_d) {
    asm volatile("{\n.reg .pred p;\n"
        "setp.ne.b32 p, %130, 0;\n"
        "wgmma.mma_async.sync.aligned.m64n256k16.f32.bf16.bf16 "
        "{%0, %1, %2, %3, %4, %5, %6, %7, %8, %9, %10, %11, %12, %13, %14, %15, %16, %17, %18, %19, %20, %21, %22, %23, %24, %25, %26, %27, %28, %29, %30, %31, %32, %33, %34, %35, %36, %37, %38, %39, %40, %41, %42, %43, %44, %45, %46, %47, %48, %49, %50, %51, %52, %53, %54, %55, %56, %57, %58, %59, %60, %61, %62, %63, %64, %65, %66, %67, %68, %69, %70, %71, %72, %73, %74, %75, %76, %77, %78, %79, %80, %81, %82, %83, %84, %85, %86, %87, %88, %89, %90, %91, %92, %93, %94, %95, %96, %97, %98, %99, %100, %101, %102, %103, %104, %105, %106, %107, %108, %109, %110, %111, %112, %113, %114, %115, %116, %117, %118, %119, %120, %121, %122, %123, %124, %125, %126, %127}, "
        "%128, %129, p, 1, 1, %131, %132;\n}\n"
        : "+f"(d[0]), "+f"(d[1]), "+f"(d[2]), "+f"(d[3]), "+f"(d[4]), "+f"(d[5]), "+f"(d[6]), "+f"(d[7]), "+f"(d[8]), "+f"(d[9]), "+f"(d[10]), "+f"(d[11]), "+f"(d[12]), "+f"(d[13]), "+f"(d[14]), "+f"(d[15]), "+f"(d[16]), "+f"(d[17]), "+f"(d[18]), "+f"(d[19]), "+f"(d[20]), "+f"(d[21]), "+f"(d[22]), "+f"(d[23]), "+f"(d[24]), "+f"(d[25]), "+f"(d[26]), "+f"(d[27]), "+f"(d[28]), "+f"(d[29]), "+f"(d[30]), "+f"(d[31]), "+f"(d[32]), "+f"(d[33]), "+f"(d[34]), "+f"(d[35]), "+f"(d[36]), "+f"(d[37]), "+f"(d[38]), "+f"(d[39]), "+f"(d[40]), "+f"(d[41]), "+f"(d[42]), "+f"(d[43]), "+f"(d[44]), "+f"(d[45]), "+f"(d[46]), "+f"(d[47]), "+f"(d[48]), "+f"(d[49]), "+f"(d[50]), "+f"(d[51]), "+f"(d[52]), "+f"(d[53]), "+f"(d[54]), "+f"(d[55]), "+f"(d[56]), "+f"(d[57]), "+f"(d[58]), "+f"(d[59]), "+f"(d[60]), "+f"(d[61]), "+f"(d[62]), "+f"(d[63]), "+f"(d[64]), "+f"(d[65]), "+f"(d[66]), "+f"(d[67]), "+f"(d[68]), "+f"(d[69]), "+f"(d[70]), "+f"(d[71]), "+f"(d[72]), "+f"(d[73]), "+f"(d[74]), "+f"(d[75]), "+f"(d[76]), "+f"(d[77]), "+f"(d[78]), "+f"(d[79]), "+f"(d[80]), "+f"(d[81]), "+f"(d[82]), "+f"(d[83]), "+f"(d[84]), "+f"(d[85]), "+f"(d[86]), "+f"(d[87]), "+f"(d[88]), "+f"(d[89]), "+f"(d[90]), "+f"(d[91]), "+f"(d[92]), "+f"(d[93]), "+f"(d[94]), "+f"(d[95]), "+f"(d[96]), "+f"(d[97]), "+f"(d[98]), "+f"(d[99]), "+f"(d[100]), "+f"(d[101]), "+f"(d[102]), "+f"(d[103]), "+f"(d[104]), "+f"(d[105]), "+f"(d[106]), "+f"(d[107]), "+f"(d[108]), "+f"(d[109]), "+f"(d[110]), "+f"(d[111]), "+f"(d[112]), "+f"(d[113]), "+f"(d[114]), "+f"(d[115]), "+f"(d[116]), "+f"(d[117]), "+f"(d[118]), "+f"(d[119]), "+f"(d[120]), "+f"(d[121]), "+f"(d[122]), "+f"(d[123]), "+f"(d[124]), "+f"(d[125]), "+f"(d[126]), "+f"(d[127])
        : "l"(da), "l"(db), "r"(scale_d), "n"(TA), "n"(TB));
}
template<int TB>
__device__ __forceinline__ void wgmma_m64n192k16_rs(float (&d)[96], uint32_t a0, uint32_t a1, uint32_t a2, uint32_t a3, uint64_t db, int scale_d) {
    asm volatile("{\n.reg .pred p;\n"
        "setp.ne.b32 p, %101, 0;\n"
        "wgmma.mma_async.sync.aligned.m64n192k16.f32.bf16.bf16 "
        "{%0, %1, %2, %3, %4, %5, %6, %7, %8, %9, %10, %11, %12, %13, %14, %15, %16, %17, %18, %19, %20, %21, %22, %23, %24, %25, %26, %27, %28, %29, %30, %31, %32, %33, %34, %35, %36, %37, %38, %39, %40, %41, %42, %43, %44, %45, %46, %47, %48, %49, %50, %51, %52, %53, %54, %55, %56, %57, %58, %59, %60, %61, %62, %63, %64, %65, %66, %67, %68, %69, %70, %71, %72, %73, %74, %75, %76, %77, %78, %79, %80, %81, %82, %83, %84, %85, %86, %87, %88, %89, %90, %91, %92, %93, %94, %95}, "
        "{%96, %97, %98, %99}, %100, p, 1, 1, %102;\n}\n"
        : "+f"(d[0]), "+f"(d[1]), "+f"(d[2]), "+f"(d[3]), "+f"(d[4]), "+f"(d[5]), "+f"(d[6]), "+f"(d[7]), "+f"(d[8]), "+f"(d[9]), "+f"(d[10]), "+f"(d[11]), "+f"(d[12]), "+f"(d[13]), "+f"(d[14]), "+f"(d[15]), "+f"(d[16]), "+f"(d[17]), "+f"(d[18]), "+f"(d[19]), "+f"(d[20]), "+f"(d[21]), "+f"(d[22]), "+f"(d[23]), "+f"(d[24]), "+f"(d[25]), "+f"(d[26]), "+f"(d[27]), "+f"(d[28]), "+f"(d[29]), "+f"(d[30]), "+f"(d[31]), "+f"(d[32]), "+f"(d[33]), "+f"(d[34]), "+f"(d[35]), "+f"(d[36]), "+f"(d[37]), "+f"(d[38]), "+f"(d[39]), "+f"(d[40]), "+f"(d[41]), "+f"(d[42]), "+f"(d[43]), "+f"(d[44]), "+f"(d[45]), "+f"(d[46]), "+f"(d[47]), "+f"(d[48]), "+f"(d[49]), "+f"(d[50]), "+f"(d[51]), "+f"(d[52]), "+f"(d[53]), "+f"(d[54]), "+f"(d[55]), "+f"(d[56]), "+f"(d[57]), "+f"(d[58]), "+f"(d[59]), "+f"(d[60]), "+f"(d[61]), "+f"(d[62]), "+f"(d[63]), "+f"(d[64]), "+f"(d[65]), "+f"(d[66]), "+f"(d[67]), "+f"(d[68]), "+f"(d[69]), "+f"(d[70]), "+f"(d[71]), "+f"(d[72]), "+f"(d[73]), "+f"(d[74]), "+f"(d[75]), "+f"(d[76]), "+f"(d[77]), "+f"(d[78]), "+f"(d[79]), "+f"(d[80]), "+f"(d[81]), "+f"(d[82]), "+f"(d[83]), "+f"(d[84]), "+f"(d[85]), "+f"(d[86]), "+f"(d[87]), "+f"(d[88]), "+f"(d[89]), "+f"(d[90]), "+f"(d[91]), "+f"(d[92]), "+f"(d[93]), "+f"(d[94]), "+f"(d[95])
        : "r"(a0), "r"(a1), "r"(a2), "r"(a3), "l"(db), "r"(scale_d), "n"(TB));
}
template<int TA, int TB>
__device__ __forceinline__ void wgmma_m64n64k16_ss(float (&d)[32], uint64_t da, uint64_t db, int scale_d) {
    asm volatile("{\n.reg .pred p;\n"
        "setp.ne.b32 p, %34, 0;\n"
        "wgmma.mma_async.sync.aligned.m64n64k16.f32.bf16.bf16 "
        "{%0, %1, %2, %3, %4, %5, %6, %7, %8, %9, %10, %11, %12, %13, %14, %15, %16, %17, %18, %19, %20, %21, %22, %23, %24, %25, %26, %27, %28, %29, %30, %31}, "
        "%32, %33, p, 1, 1, %35, %36;\n}\n"
        : "+f"(d[0]), "+f"(d[1]), "+f"(d[2]), "+f"(d[3]), "+f"(d[4]), "+f"(d[5]), "+f"(d[6]), "+f"(d[7]), "+f"(d[8]), "+f"(d[9]), "+f"(d[10]), "+f"(d[11]), "+f"(d[12]), "+f"(d[13]), "+f"(d[14]), "+f"(d[15]), "+f"(d[16]), "+f"(d[17]), "+f"(d[18]), "+f"(d[19]), "+f"(d[20]), "+f"(d[21]), "+f"(d[22]), "+f"(d[23]), "+f"(d[24]), "+f"(d[25]), "+f"(d[26]), "+f"(d[27]), "+f"(d[28]), "+f"(d[29]), "+f"(d[30]), "+f"(d[31])
        : "l"(da), "l"(db), "r"(scale_d), "n"(TA), "n"(TB));
}
template<int TB>
__device__ __forceinline__ void wgmma_m64n64k16_rs_z(float (&d)[32], uint32_t a0, uint32_t a1, uint32_t a2, uint32_t a3, uint64_t db) {
    asm volatile("{\n.reg .pred p;\n"
        "setp.ne.b32 p, 0, 0;\n"
        "wgmma.mma_async.sync.aligned.m64n64k16.f32.bf16.bf16 "
        "{%0, %1, %2, %3, %4, %5, %6, %7, %8, %9, %10, %11, %12, %13, %14, %15, %16, %17, %18, %19, %20, %21, %22, %23, %24, %25, %26, %27, %28, %29, %30, %31}, "
        "{%32, %33, %34, %35}, %36, p, 1, 1, %37;\n}\n"
        : "=f"(d[0]), "=f"(d[1]), "=f"(d[2]), "=f"(d[3]), "=f"(d[4]), "=f"(d[5]), "=f"(d[6]), "=f"(d[7]), "=f"(d[8]), "=f"(d[9]), "=f"(d[10]), "=f"(d[11]), "=f"(d[12]), "=f"(d[13]), "=f"(d[14]), "=f"(d[15]), "=f"(d[16]), "=f"(d[17]), "=f"(d[18]), "=f"(d[19]), "=f"(d[20]), "=f"(d[21]), "=f"(d[22]), "=f"(d[23]), "=f"(d[24]), "=f"(d[25]), "=f"(d[26]), "=f"(d[27]), "=f"(d[28]), "=f"(d[29]), "=f"(d[30]), "=f"(d[31])
        : "r"(a0), "r"(a1), "r"(a2), "r"(a3), "l"(db), "n"(TB));
}
template<int TB>
__device__ __forceinline__ void wgmma_m64n128k16_rs_z(float (&d)[64], uint32_t a0, uint32_t a1, uint32_t a2, uint32_t a3, uint64_t db) {
    asm volatile("{\n.reg .pred p;\n"
        "setp.ne.b32 p, 0, 0;\n"
        "wgmma.mma_async.sync.aligned.m64n128k16.f32.bf16.bf16 "
        "{%0, %1, %2, %3, %4, %5, %6, %7, %8, %9, %10, %11, %12, %13, %14, %15, %16, %17, %18, %19, %20, %21, %22, %23, %24, %25, %26, %27, %28, %29, %30, %31, %32, %33, %34, %35, %36, %37, %38, %39, %40, %41, %42, %43, %44, %45, %46, %47, %48, %49, %50, %51, %52, %53, %54, %55, %56, %57, %58, %59, %60, %61, %62, %63}, "
        "{%64, %65, %66, %67}, %68, p, 1, 1, %69;\n}\n"
        : "=f"(d[0]), "=f"(d[1]), "=f"(d[2]), "=f"(d[3]), "=f"(d[4]), "=f"(d[5]), "=f"(d[6]), "=f"(d[7]), "=f"(d[8]), "=f"(d[9]), "=f"(d[10]), "=f"(d[11]), "=f"(d[12]), "=f"(d[13]), "=f"(d[14]), "=f"(d[15]), "=f"(d[16]), "=f"(d[17]), "=f"(d[18]), "=f"(d[19]), "=f"(d[20]), "=f"(d[21]), "=f"(d[22]), "=f"(d[23]), "=f"(d[24]), "=f"(d[25]), "=f"(d[26]), "=f"(d[27]), "=f"(d[28]), "=f"(d[29]), "=f"(d[30]), "=f"(d[31]), "=f"(d[32]), "=f"(d[33]), "=f"(d[34]), "=f"(d[35]), "=f"(d[36]), "=f"(d[37]), "=f"(d[38]), "=f"(d[39]), "=f"(d[40]), "=f"(d[41]), "=f"(d[42]), "=f"(d[43]), "=f"(d[44]), "=f"(d[45]), "=f"(d[46]), "=f"(d[47]), "=f"(d[48]), "=f"(d[49]), "=f"(d[50]), "=f"(d[51]), "=f"(d[52]), "=f"(d[53]), "=f"(d[54]), "=f"(d[55]), "=f"(d[56]), "=f"(d[57]), "=f"(d[58]), "=f"(d[59]), "=f"(d[60]), "=f"(d[61]), "=f"(d[62]), "=f"(d[63])
        : "r"(a0), "r"(a1), "r"(a2), "r"(a3), "l"(db), "n"(TB));
}

constexpr int NSLOT      = 6;
constexpr int SLOT_BYTES = 32768;
constexpr int STG_OFF    = NSLOT * SLOT_BYTES;
constexpr int BAR_OFF    = STG_OFF + 32768;
constexpr int ONES_OFF   = BAR_OFF + 256;
constexpr int SMEM_BYTES = BAR_OFF + 512 + 1024;
constexpr int NTHREADS   = 384;

struct Params {
    CUtensorMap ckv;
    CUtensorMap wuk;
    CUtensorMap wuv;
    CUtensorMap kv_st;
    CUtensorMap kv_ld;
    CUtensorMap xn;
    CUtensorMap wq;
    CUtensorMap ctx_st;
    CUtensorMap ctx_ld;
    CUtensorMap wo;
    CUtensorMap w2;
    CUtensorMap uT;
    CUtensorMap w1;
    CUtensorMap h;
    const bf16* b1;
};

struct Ctx {
    uint32_t sbase;
    uint32_t full0;
    uint32_t empty0;
    uint32_t empty_rel;
    uint32_t rank;
    int wg;
};
struct Ring {
    uint32_t idx, phase;
    __device__ __forceinline__ void adv() { if (++idx == NSLOT) { idx = 0; phase ^= 1; } }
    __device__ __forceinline__ void adv2() { idx += 2; if (idx >= NSLOT) { idx -= NSLOT; phase ^= 1; } }
};
__device__ __forceinline__ uint32_t slot_addr(const Ctx& c, uint32_t idx) { return c.sbase + idx * SLOT_BYTES; }
__device__ __forceinline__ void wait_full(const Ctx& c, const Ring& r) { mbar_wait(c.full0 + 8 * r.idx, r.phase); }
__device__ __forceinline__ void release(const Ctx& c, uint32_t idx) {
    __syncwarp();
    if ((threadIdx.x & 31) < 2) mbar_arrive_cluster(c.empty_rel + 8 * idx);
}
__device__ __forceinline__ uint32_t acquire(const Ctx& c, const Ring& r, uint32_t bytes) {
    mbar_wait(c.empty0 + 8 * r.idx, r.phase ^ 1);
    mbar_expect_tx(c.full0 + 8 * r.idx, bytes);
    return slot_addr(c, r.idx);
}

__device__ __forceinline__ void kv_producer(const Params& p, const Ctx& c, Ring& r, int m, int t0, int t1) {
    for (int ch = 0; ch < 4; ch++) {
        uint32_t s = acquire(c, r, 32768);
        uint32_t bar = c.full0 + 8 * r.idx;
        tma_load(s, &p.ckv, ch * 128, m * 128, bar);
        tma_load(s + 16384, &p.ckv, ch * 128 + 64, m * 128, bar);
        r.adv();
    }
    for (int t = t0; t < t1; t++) {
        const CUtensorMap* wm = (t < 64) ? &p.wuk : &p.wuv;
        int col = (t & 63) * 64;
        for (int half = 0; half < 2; half++) {
            uint32_t s = acquire(c, r, 32768);
            tma_load_mc(s + c.rank * 16384, wm, col, half * 256 + c.rank * 128, c.full0 + 8 * r.idx);
            r.adv();
        }
    }
}

__device__ __forceinline__ void kv_epilogue(const Params& p, const Ctx& c, float (&acc)[32], int t, int m, int buf) {
    const int tid = threadIdx.x, wg = c.wg, warp = (tid >> 5) & 3, lane = tid & 31;
    uint32_t stg = c.sbase + STG_OFF + wg * 16384 + buf * 8192;
    const int mi = lane >> 3;
    const int row = warp * 16 + (lane & 7) + 8 * (mi & 1);
#pragma unroll
    for (int jj = 0; jj < 4; jj++) {
        int chunk = 2 * jj + (mi >> 1);
        stmatrix_x4(stg + row * 128 + ((chunk ^ (row & 7)) << 4),
                    pack_bf16(acc[8 * jj + 0], acc[8 * jj + 1]), pack_bf16(acc[8 * jj + 2], acc[8 * jj + 3]),
                    pack_bf16(acc[8 * jj + 4], acc[8 * jj + 5]), pack_bf16(acc[8 * jj + 6], acc[8 * jj + 7]));
    }
    fence_async_smem();
    if ((tid & 127) == 0) bulk_wait_read<0>();
    named_bar_sync(1 + wg, 128);
    if ((tid & 127) == 0) {
        tma_store(&p.kv_st, stg, (t & 1) * 64, (t >> 1) * SEQ + m * 128 + wg * 64);
        bulk_commit();
    }
}

__device__ __forceinline__ void kv_issue(const Ctx& c, const Ring& r, float (&acc)[32], const uint32_t (&a)[128], const int half) {
    wait_full(c, r);
    uint32_t s = slot_addr(c, r.idx);
    wg_fence();
    if (half == 0) {
#pragma unroll
        for (int kk = 0; kk < 16; kk++) {
            if (kk == 0) wgmma_m64n64k16_rs_z<1>(acc, a[0], a[1], a[2], a[3], make_desc(s, 8192, 1024));
            else wgmma_m64n64k16_rs<1>(acc, a[4 * kk], a[4 * kk + 1], a[4 * kk + 2], a[4 * kk + 3], make_desc(s + kk * 2048, 8192, 1024), 1);
        }
    } else {
#pragma unroll
        for (int kk = 0; kk < 16; kk++)
            wgmma_m64n64k16_rs<1>(acc, a[64 + 4 * kk], a[64 + 4 * kk + 1], a[64 + 4 * kk + 2], a[64 + 4 * kk + 3], make_desc(s + kk * 2048, 8192, 1024), 1);
    }
    wg_commit();
}

__device__ __forceinline__ void kv_consumer(const Params& p, const Ctx& c, Ring& r, int m, int t0, int t1) {
    const int tid = threadIdx.x, wg = c.wg, warp = (tid >> 5) & 3, lane = tid & 31;
    uint32_t a[128];
    {
        const int mi = lane >> 3;
        const int row = wg * 64 + warp * 16 + (lane & 7) + 8 * (mi & 1);
#pragma unroll
        for (int ch = 0; ch < 4; ch++) {
            wait_full(c, r);
            uint32_t s = slot_addr(c, r.idx);
#pragma unroll
            for (int b = 0; b < 2; b++)
#pragma unroll
                for (int kk = 0; kk < 4; kk++) {
                    int chunk = 2 * kk + (mi >> 1);
                    int i = (ch * 8 + b * 4 + kk) * 4;
                    ldmatrix_x4(a[i], a[i + 1], a[i + 2], a[i + 3], s + b * 16384 + row * 128 + ((chunk ^ (row & 7)) << 4));
                }
            release(c, r.idx);
            r.adv();
        }
    }
    PROF_STAMP(1, 1);
    float acc0[32], acc1[32];
    uint32_t prev = 0;
    int t = t0;
    kv_issue(c, r, acc0, a, 0); prev = r.idx; r.adv();
    kv_issue(c, r, acc0, a, 1);
    wg_wait<1>(); release(c, prev); prev = r.idx; r.adv();
    t++;
    while (true) {
        if (t >= t1) { wg_wait<0>(); fence_regs(acc0); release(c, prev); kv_epilogue(p, c, acc0, t - 1, m, 0); break; }
        kv_issue(c, r, acc1, a, 0);
        wg_wait<1>(); fence_regs(acc0); release(c, prev); prev = r.idx; r.adv();
        kv_epilogue(p, c, acc0, t - 1, m, 0);
        kv_issue(c, r, acc1, a, 1);
        wg_wait<1>(); release(c, prev); prev = r.idx; r.adv();
        t++;
        if (t >= t1) { wg_wait<0>(); fence_regs(acc1); release(c, prev); kv_epilogue(p, c, acc1, t - 1, m, 1); break; }
        kv_issue(c, r, acc0, a, 0);
        wg_wait<1>(); fence_regs(acc1); release(c, prev); prev = r.idx; r.adv();
        kv_epilogue(p, c, acc1, t - 1, m, 1);
        kv_issue(c, r, acc0, a, 1);
        wg_wait<1>(); release(c, prev); prev = r.idx; r.adv();
        t++;
    }
    PROF_STAMP(1, 2);
    if ((tid & 127) == 0) bulk_wait<0>();
}

template<int AMODE>
__device__ __forceinline__ void g320_producer(const Ctx& c, Ring& r, const CUtensorMap* amap, int a_m0, int a_k0,
                                              const CUtensorMap* bmap, int b_n0, int b_k0, int nsteps) {
    for (int st = 0; st < nsteps; st++) {
        uint32_t x = acquire(c, r, 32768);
        uint32_t bx = c.full0 + 8 * r.idx;
        if (AMODE == 0) {
            tma_load(x, amap, a_k0 + st * 64, a_m0, bx);
        } else {
            tma_load(x, amap, a_m0, a_k0 + st * 64, bx);
            tma_load(x + 8192, amap, a_m0 + 64, a_k0 + st * 64, bx);
        }
        uint32_t par = (st + c.rank) & 1;
        tma_load_mc(x + 16384 + par * 8192, bmap, b_n0 + par * 64, b_k0 + st * 64, bx);
        r.adv();
        uint32_t y = acquire(c, r, 24576);
        uint32_t by = c.full0 + 8 * r.idx;
        if (par == 0) {
            tma_load_mc(y, bmap, b_n0 + 128, b_k0 + st * 64, by);
            tma_load_mc(y + 16384, bmap, b_n0 + 256, b_k0 + st * 64, by);
        } else {
            tma_load_mc(y + 8192, bmap, b_n0 + 192, b_k0 + st * 64, by);
        }
        r.adv();
    }
}

template<int AMODE>
__device__ __forceinline__ void g320_segment(const Ctx& c, Ring& r, float (&acc0)[64], float (&acc1)[96], int nsteps,
                                             int& first, uint32_t& prevx, uint32_t& prevy) {
    const int wg = c.wg;
    for (int st = 0; st < nsteps; st++) {
        Ring rx = r; r.adv();
        Ring ry = r; r.adv();
        wait_full(c, rx);
        wait_full(c, ry);
        uint32_t x = slot_addr(c, rx.idx), y = slot_addr(c, ry.idx);
        wg_fence();
#pragma unroll
        for (int kk = 0; kk < 4; kk++) {
            uint64_t da = (AMODE == 0) ? make_desc(x + wg * 8192 + kk * 32, 16, 1024) : make_desc(x + wg * 8192 + kk * 2048, 8192, 1024);
            const int sd = 1;
            wgmma_m64n128k16_ss<AMODE, 1>(acc0, da, make_desc(x + 16384 + kk * 2048, 8192, 1024), sd);
            wgmma_m64n192k16_ss<AMODE, 1>(acc1, da, make_desc(y + kk * 2048, 8192, 1024), sd);
        }
        wg_commit();
        if (!first) { wg_wait<1>(); release(c, prevx); release(c, prevy); }
        first = 0;
        prevx = rx.idx; prevy = ry.idx;
    }
}

__device__ __forceinline__ float gelu_tanh(float u) {
    float z2 = 1.5957691216057308f * u * fmaf(0.044715f * u, u, 1.0f);
    float e = ex2(-1.4426950408889634f * z2);
    return __fdividef(u, 1.0f + e);
}

__device__ __forceinline__ void b1_producer(const Params& p, const Ctx& c, Ring& r, int m, int nh) {
    g320_producer<1>(c, r, &p.w1, m * 128, 0, &p.h, nh * 320, 0, 32);
}
__device__ __forceinline__ void b1_consumer(const Params& p, const Ctx& c, Ring& r, int m, int nh) {
    const int tid = threadIdx.x, wg = c.wg, warp = (tid >> 5) & 3, lane = tid & 31;
    float acc0[64], acc1[96];
#pragma unroll
    for (int i = 0; i < 64; i++) acc0[i] = 0.f;
#pragma unroll
    for (int i = 0; i < 96; i++) acc1[i] = 0.f;
    int first = 1; uint32_t px = 0, py = 0;
    g320_segment<1>(c, r, acc0, acc1, 32, first, px, py);
    wg_wait<0>(); fence_regs(acc0); fence_regs(acc1);
    release(c, px); release(c, py);
    PROF_STAMP(1, 2);
    const int f0 = m * 128 + wg * 64 + warp * 16 + (lane >> 2);
    if (f0 < FF) {
        float bb0 = __bfloat162float(p.b1[f0]), bb1 = __bfloat162float(p.b1[f0 + 8]);
        uint32_t* o0 = (uint32_t*)(g_uT + (size_t)f0 * DM + nh * 320 + (lane & 3) * 2);
        uint32_t* o1 = o0 + 8 * DM / 2;
#pragma unroll
        for (int j = 0; j < 16; j++) {
            o0[j * 4] = pack_bf16(gelu_tanh(bf16r(bf16r(acc0[4 * j]) + bb0)), gelu_tanh(bf16r(bf16r(acc0[4 * j + 1]) + bb0)));
            o1[j * 4] = pack_bf16(gelu_tanh(bf16r(bf16r(acc0[4 * j + 2]) + bb1)), gelu_tanh(bf16r(bf16r(acc0[4 * j + 3]) + bb1)));
        }
#pragma unroll
        for (int j = 0; j < 24; j++) {
            o0[64 + j * 4] = pack_bf16(gelu_tanh(bf16r(bf16r(acc1[4 * j]) + bb0)), gelu_tanh(bf16r(bf16r(acc1[4 * j + 1]) + bb0)));
            o1[64 + j * 4] = pack_bf16(gelu_tanh(bf16r(bf16r(acc1[4 * j + 2]) + bb1)), gelu_tanh(bf16r(bf16r(acc1[4 * j + 3]) + bb1)));
        }
    }
}

__device__ __forceinline__ void p3_chunks(int kq, int& c0, int& nc) { c0 = kq * 7; nc = (kq == 3) ? 6 : 7; }
__device__ __forceinline__ void p3_producer(const Params& p, const Ctx& c, Ring& r, int m, int nh, int kq) {
    int c0, nc; p3_chunks(kq, c0, nc);
    g320_producer<1>(c, r, &p.w2, m * 128, c0 * 64, &p.uT, nh * 320, c0 * 64, nc);
    g320_producer<0>(c, r, &p.ctx_ld, m * 128, kq * 1024, &p.wo, nh * 320, kq * 1024, 16);
}
__device__ __forceinline__ void red_v2(float* ptr, float a, float b) {
    asm volatile("red.global.add.v2.f32 [%0], {%1, %2};" :: "l"(ptr), "f"(a), "f"(b) : "memory");
}
__device__ __forceinline__ void p3_consumer(const Params& p, const Ctx& c, Ring& r, int m, int nh, int kq) {
    const int tid = threadIdx.x, wg = c.wg, warp = (tid >> 5) & 3, lane = tid & 31;
    float acc0[64], acc1[96];
#pragma unroll
    for (int i = 0; i < 64; i++) acc0[i] = 0.f;
#pragma unroll
    for (int i = 0; i < 96; i++) acc1[i] = 0.f;
    int first = 1; uint32_t px = 0, py = 0;
    int c0, nc; p3_chunks(kq, c0, nc);
    g320_segment<1>(c, r, acc0, acc1, nc, first, px, py);
    PROF_STAMP(3, 1);
    g320_segment<0>(c, r, acc0, acc1, 16, first, px, py);
    wg_wait<0>(); fence_regs(acc0); fence_regs(acc1);
    release(c, px); release(c, py);
    PROF_STAMP(3, 2);
    const int row = m * 128 + wg * 64 + warp * 16 + (lane >> 2);
    float* o0 = g_acc + (size_t)row * DM + nh * 320 + (lane & 3) * 2;
    float* o1 = o0 + 8 * DM;
#pragma unroll
    for (int j = 0; j < 16; j++) {
        red_v2(o0 + j * 8, acc0[4 * j], acc0[4 * j + 1]);
        red_v2(o1 + j * 8, acc0[4 * j + 2], acc0[4 * j + 3]);
    }
#pragma unroll
    for (int j = 0; j < 24; j++) {
        red_v2(o0 + 128 + j * 8, acc1[4 * j], acc1[4 * j + 1]);
        red_v2(o1 + 128 + j * 8, acc1[4 * j + 2], acc1[4 * j + 3]);
    }
}

__device__ __forceinline__ int att_row_off(uint32_t rank, int wg) { return rank == 0 ? (wg == 0 ? 0 : 192) : (wg == 0 ? 64 : 128); }

__device__ __forceinline__ void att_producer(const Params& p, const Ctx& c, Ring& r, int jb, int hp) {
    const int R = jb * 256;
    const int r0 = R + att_row_off(c.rank, 0), r1 = R + att_row_off(c.rank, 1);
    for (int kp = 0; kp < 5; kp++) {
        uint32_t s = acquire(c, r, 32768);
        uint32_t bar = c.full0 + 8 * r.idx;
        tma_load(s, &p.xn, kp * 128, r0, bar);
        tma_load(s + 8192, &p.xn, kp * 128, r1, bar);
        tma_load(s + 16384, &p.xn, kp * 128 + 64, r0, bar);
        tma_load(s + 24576, &p.xn, kp * 128 + 64, r1, bar);
        r.adv();
        for (int ks = 0; ks < 2; ks++) {
            s = acquire(c, r, 32768);
            bar = c.full0 + 8 * r.idx;
            int krow = kp * 128 + ks * 64;
            tma_load_mc(s + c.rank * 16384, &p.wq, hp * 256 + c.rank * 128, krow, bar);
            tma_load_mc(s + c.rank * 16384 + 8192, &p.wq, hp * 256 + c.rank * 128 + 64, krow, bar);
            r.adv();
        }
    }
    const int nt = 2 * jb + 2;
    for (int hh = 0; hh < 2; hh++) {
        const int head = hp * 2 + hh;
        for (int j = 0; j < nt; j++) {
            uint32_t s = acquire(c, r, 32768);
            tma_load_mc(s + c.rank * 16384, &p.kv_ld, c.rank * 64, head * SEQ + j * 128, c.full0 + 8 * r.idx);
            r.adv();
            s = acquire(c, r, 32768);
            tma_load_mc(s + c.rank * 16384, &p.kv_ld, c.rank * 64, (32 + head) * SEQ + j * 128, c.full0 + 8 * r.idx);
            r.adv();
        }
    }
}

#define ONES_MMA 0
constexpr float SM_SCALE = 0.08838834764831845f * 1.4426950408889634f;

template<int HALF>
__device__ __forceinline__ void att_qk(const Ctx& c, uint32_t ks, float (&s)[32], const uint32_t (&q)[32], uint32_t ra0, uint32_t ra1) {
    const uint64_t dneg = (uint64_t)(((c.sbase + ONES_OFF) & 0x3FFFF) >> 4) | ((uint64_t)(128 >> 4) << 16);
    wg_fence();
    wgmma_m64n64k16_rs_z<0>(s, ra0, ra1, 0u, 0u, dneg);
#pragma unroll
    for (int kk = 0; kk < 8; kk++)
        wgmma_m64n64k16_rs<0>(s, q[4 * kk], q[4 * kk + 1], q[4 * kk + 2], q[4 * kk + 3],
                              make_desc(ks + (kk >> 2) * 16384 + HALF * 8192 + (kk & 3) * 32, 16, 1024), 1);
    wg_commit();
}
template<int HALF>
__device__ __forceinline__ void att_pv(uint32_t vs, float (&o)[64], const uint32_t (&pp)[16]) {
    wg_fence();
#pragma unroll
    for (int kk = 0; kk < 4; kk++)
        wgmma_m64n128k16_rs<1>(o, pp[4 * kk], pp[4 * kk + 1], pp[4 * kk + 2], pp[4 * kk + 3],
                               make_desc(vs + (HALF * 4 + kk) * 2048, 16384, 1024), 1);
    wg_commit();
}
__device__ __forceinline__ void att_mask(float (&s)[32]) {
    const int lane = threadIdx.x & 31;
    const int rel = ((threadIdx.x >> 5) & 3) * 16 + (lane >> 2) - 2 * (lane & 3);
#pragma unroll
    for (int j = 0; j < 8; j++) {
        if (8 * j + 0 > rel)     s[4 * j + 0] = -INFINITY;
        if (8 * j + 1 > rel)     s[4 * j + 1] = -INFINITY;
        if (8 * j + 0 > rel + 8) s[4 * j + 2] = -INFINITY;
        if (8 * j + 1 > rel + 8) s[4 * j + 3] = -INFINITY;
    }
}

__device__ __forceinline__ void turn_wait(const Ctx& c) { named_bar_sync(3 + c.wg, 256); }
__device__ __forceinline__ void turn_pass(const Ctx& c) { named_bar_arrive(4 - c.wg, 256); }
constexpr float REF_MARGIN = 40.0f;

template<bool MASK>
__device__ __forceinline__ void att_exp_pack(const float (&s)[32], uint32_t (&pp)[16], float (&t)[4]) {
    const int lane = threadIdx.x & 31;
    const int rel = ((threadIdx.x >> 5) & 3) * 16 + (lane >> 2) - 2 * (lane & 3);
    t[0] = t[1] = t[2] = t[3] = 0.f;
#pragma unroll
    for (int j = 0; j < 8; j++) {
        float e0 = ex2(s[4 * j + 0]);
        float e1 = ex2(s[4 * j + 1]);
        float e2 = ex2(s[4 * j + 2]);
        float e3 = ex2(s[4 * j + 3]);
        if (MASK) {
            if (8 * j + 0 > rel)     e0 = 0.f;
            if (8 * j + 1 > rel)     e1 = 0.f;
            if (8 * j + 0 > rel + 8) e2 = 0.f;
            if (8 * j + 1 > rel + 8) e3 = 0.f;
        }
        t[0] += e0; t[1] += e1; t[2] += e2; t[3] += e3;
        pp[2 * j] = pack_bf16(e0, e1);
        pp[2 * j + 1] = pack_bf16(e2, e3);
    }
}
__device__ __forceinline__ void att_newref(const float (&s)[32], float& r0, float& r1, float& d0, float& d1, bool first) {
    float x0 = fmaxf(s[0], s[1]), x1 = fmaxf(s[2], s[3]), y0 = fmaxf(s[4], s[5]), y1 = fmaxf(s[6], s[7]);
#pragma unroll
    for (int j = 2; j < 8; j += 2) {
        x0 = fmaxf(x0, fmaxf(s[4 * j], s[4 * j + 1]));
        x1 = fmaxf(x1, fmaxf(s[4 * j + 2], s[4 * j + 3]));
        y0 = fmaxf(y0, fmaxf(s[4 * j + 4], s[4 * j + 5]));
        y1 = fmaxf(y1, fmaxf(s[4 * j + 6], s[4 * j + 7]));
    }
    x0 = fmaxf(x0, y0); x1 = fmaxf(x1, y1);
    x0 = fmaxf(x0, __shfl_xor_sync(0xffffffffu, x0, 1));
    x1 = fmaxf(x1, __shfl_xor_sync(0xffffffffu, x1, 1));
    x0 = fmaxf(x0, __shfl_xor_sync(0xffffffffu, x0, 2));
    x1 = fmaxf(x1, __shfl_xor_sync(0xffffffffu, x1, 2));
    float n0 = bf16r(r0 + x0 + REF_MARGIN), n1 = bf16r(r1 + x1 + REF_MARGIN);
    if (!first) { n0 = fmaxf(n0, r0); n1 = fmaxf(n1, r1); }
    d0 = n0 - r0; d1 = n1 - r1;
    r0 = n0; r1 = n1;
}
__device__ __forceinline__ void att_shift(float (&s)[32], float d0, float d1) {
#pragma unroll
    for (int i = 0; i < 8; i++) {
        s[4 * i + 0] -= d0; s[4 * i + 1] -= d0;
        s[4 * i + 2] -= d1; s[4 * i + 3] -= d1;
    }
}
__device__ __forceinline__ uint32_t ref_frag(float r) {
    return ((threadIdx.x & 3) == 0) ? (__float_as_uint(r) >> 16) : 0u;
}
__device__ __forceinline__ void att_softmax(float (&s)[32], float (&so)[32], bool other_live, bool mask, uint32_t (&pp)[16], float (&o)[64], float (&ls)[4],
                                            float& r0, float& r1, uint32_t& ra0, uint32_t& ra1, int dbg) {
    float t[4];
    if (mask) att_exp_pack<true>(s, pp, t); else att_exp_pack<false>(s, pp, t);
    bool bad = !((t[0] + t[1]) + (t[2] + t[3]) < 2.0f);
    if (__builtin_expect(__any_sync(0xffffffffu, bad), 0)) {
        wg_wait<0>(); fence_regs(o); fence_regs(so);
        if (mask) att_mask(s);
        float d0, d1;
        att_newref(s, r0, r1, d0, d1, false);
        const float a0 = ex2(-d0), a1 = ex2(-d1);
        ls[0] *= a0; ls[1] *= a0; ls[2] *= a1; ls[3] *= a1;
#pragma unroll
        for (int i = 0; i < 16; i++) {
            o[4 * i + 0] *= a0; o[4 * i + 1] *= a0;
            o[4 * i + 2] *= a1; o[4 * i + 3] *= a1;
        }
        att_shift(s, d0, d1);
        if (other_live) att_shift(so, d0, d1);
        att_exp_pack<false>(s, pp, t);
        ra0 = ref_frag(r0); ra1 = ref_frag(r1);
    }
    ls[0] += t[0]; ls[1] += t[1]; ls[2] += t[2]; ls[3] += t[3];
}

__device__ __forceinline__ void att_head(const Params& p, const Ctx& c, Ring& r, const uint32_t (&q)[32], int nt_cta, int row_base  ,
                                         int head, float (&o)[64], float& inv0, float& inv1) {
    const int nh = (row_base >> 6) + 1;
    Ring kc = r, vc = r; vc.adv();
    float sa[32], sb[32];
    uint32_t pa[16], pb[16];
    float ls[4] = {0.f, 0.f, 0.f, 0.f};
    float r0 = 0.f, r1 = 0.f;
    int vpend = -1;
#pragma unroll
    for (int i = 0; i < 64; i++) o[i] = 0.f;
#pragma unroll
    for (int i = 0; i < 32; i++) sb[i] = 0.f;
    const int pslot = (nt_cta > 8 ? 0 : 2) + (head & 1);
    PROF_ITER(pslot, 0);
    wait_full(c, kc);
    att_qk<0>(c, slot_addr(c, kc.idx), sa, q, 0u, 0u);
    wg_wait<0>(); fence_regs(sa);
    if (nh == 1) { release(c, kc.idx); kc.adv2(); att_mask(sa); }
    {
        float d0, d1;
        att_newref(sa, r0, r1, d0, d1, true);
        att_shift(sa, d0, d1);
    }
    uint32_t ra0 = ref_frag(r0), ra1 = ref_frag(r1);
    for (int h = 0;; h += 2) {
        PROF_ITER(pslot, (3 * (h >> 1) + 3) & 63);
        const bool moreB = h + 1 < nh;
        if (moreB) att_qk<1>(c, slot_addr(c, kc.idx), sb, q, ra0, ra1);
        att_softmax(sa, sb, moreB, !moreB, pa, o, ls, r0, r1, ra0, ra1, h);
        wait_full(c, vc);
        att_pv<0>(slot_addr(c, vc.idx), o, pa);
        if (!moreB) {
            wg_wait<0>(); fence_regs(o);
            if (vpend >= 0) release(c, vpend);
            release(c, vc.idx); vc.adv2();
            break;
        }
        wg_wait<1>(); fence_regs(sb); fence_regs_u(pb);
        if (vpend >= 0) release(c, vpend);
        release(c, kc.idx); kc.adv2();
        PROF_ITER(pslot, (3 * (h >> 1) + 4) & 63);
        const bool moreA = h + 2 < nh;
        if (moreA) {
            wait_full(c, kc);
            att_qk<0>(c, slot_addr(c, kc.idx), sa, q, ra0, ra1);
        }
        att_softmax(sb, sa, moreA, !moreA, pb, o, ls, r0, r1, ra0, ra1, h + 1);
        att_pv<1>(slot_addr(c, vc.idx), o, pb);
        vpend = vc.idx; vc.adv2();
        if (!moreA) {
            wg_wait<0>(); fence_regs(o);
            release(c, vpend);
            break;
        }
        PROF_ITER(pslot, (3 * (h >> 1) + 5) & 63);
        wg_wait<1>(); fence_regs(sa); fence_regs_u(pa);
        if (h + 3 == nh) { release(c, kc.idx); kc.adv2(); }
    }
    for (int j = (nh + 1) >> 1; j < nt_cta; j++) {
        wait_full(c, kc); release(c, kc.idx); kc.adv2();
        wait_full(c, vc); release(c, vc.idx); vc.adv2();
    }
    r = kc;
    ls[0] += ls[1]; ls[2] += ls[3];
    ls[0] += __shfl_xor_sync(0xffffffffu, ls[0], 1);
    ls[2] += __shfl_xor_sync(0xffffffffu, ls[2], 1);
    ls[0] += __shfl_xor_sync(0xffffffffu, ls[0], 2);
    ls[2] += __shfl_xor_sync(0xffffffffu, ls[2], 2);
    inv0 = __fdividef(1.0f, ls[0]);
    inv1 = __fdividef(1.0f, ls[2]);
}

__device__ __forceinline__ void att_store(const Params& p, const Ctx& c, const float (&o)[64], float inv0, float inv1, int row_base, int head) {
    const int tid = threadIdx.x, wg = c.wg, warp = (tid >> 5) & 3, lane = tid & 31;
    uint32_t stg = c.sbase + STG_OFF + wg * 16384;
    const int mi = lane >> 3;
    const int row = warp * 16 + (lane & 7) + 8 * (mi & 1);
#pragma unroll
    for (int jj = 0; jj < 8; jj++) {
        int chunk = 2 * (jj & 3) + (mi >> 1);
        stmatrix_x4(stg + (jj >> 2) * 8192 + row * 128 + ((chunk ^ (row & 7)) << 4),
                    pack_bf16(o[8 * jj + 0] * inv0, o[8 * jj + 1] * inv0), pack_bf16(o[8 * jj + 2] * inv1, o[8 * jj + 3] * inv1),
                    pack_bf16(o[8 * jj + 4] * inv0, o[8 * jj + 5] * inv0), pack_bf16(o[8 * jj + 6] * inv1, o[8 * jj + 7] * inv1));
    }
    fence_async_smem();
    named_bar_sync(1 + wg, 128);
    if ((tid & 127) == 0) {
        tma_store(&p.ctx_st, stg, head * HD, row_base);
        tma_store(&p.ctx_st, stg + 8192, head * HD + 64, row_base);
        bulk_commit();
    }
}

__device__ __forceinline__ void att_consumer(const Params& p, const Ctx& c, Ring& r, int jb, int hp) {
    const int tid = threadIdx.x, wg = c.wg;
    const int row_base = jb * 256 + att_row_off(c.rank, wg);
    const uint32_t stash = c.sbase + STG_OFF + wg * 16384 + (tid & 127) * 16;
    uint32_t q[32];
    {
        float qa[128];
#pragma unroll
        for (int i = 0; i < 128; i++) qa[i] = 0.f;
        uint32_t prevb = 0, preva = 0;
#pragma unroll 1
        for (int kp = 0; kp < 5; kp++) {
            Ring ra = r; r.adv();
            wait_full(c, ra);
            uint32_t sa = slot_addr(c, ra.idx) + wg * 8192;
#pragma unroll
            for (int ks = 0; ks < 2; ks++) {
                Ring rb = r; r.adv();
                wait_full(c, rb);
                uint32_t sb = slot_addr(c, rb.idx);
                wg_fence();
#pragma unroll
                for (int kk = 0; kk < 4; kk++)
                    wgmma_m64n256k16_ss<0, 1>(qa, make_desc(sa + ks * 16384 + kk * 32, 16, 1024), make_desc(sb + kk * 2048, 8192, 1024),
                                              1);
                wg_commit();
                if (ks > 0 || kp > 0) {
                    wg_wait<1>();
                    release(c, prevb);
                    if (ks == 0) release(c, preva);
                }
                prevb = rb.idx;
            }
            preva = ra.idx;
        }
        wg_wait<0>(); fence_regs(qa);
        release(c, prevb); release(c, preva);
        if ((tid & 127) == 0) bulk_wait_read<0>();
        named_bar_sync(1 + wg, 128);
#pragma unroll
        for (int i = 0; i < 32; i++) q[i] = pack_bf16(qa[2 * i] * SM_SCALE, qa[2 * i + 1] * SM_SCALE);
#pragma unroll
        for (int i = 0; i < 8; i++) {
            uint32_t v0 = pack_bf16(qa[64 + 8 * i + 0] * SM_SCALE, qa[64 + 8 * i + 1] * SM_SCALE), v1 = pack_bf16(qa[64 + 8 * i + 2] * SM_SCALE, qa[64 + 8 * i + 3] * SM_SCALE);
            uint32_t v2 = pack_bf16(qa[64 + 8 * i + 4] * SM_SCALE, qa[64 + 8 * i + 5] * SM_SCALE), v3 = pack_bf16(qa[64 + 8 * i + 6] * SM_SCALE, qa[64 + 8 * i + 7] * SM_SCALE);
            asm volatile("st.shared.v4.b32 [%0], {%1, %2, %3, %4};" :: "r"(stash + i * 2048), "r"(v0), "r"(v1), "r"(v2), "r"(v3) : "memory");
        }
    }
    PROF_STAMP(2, jb >= 4 ? 1 : 4);
    const int nt = 2 * jb + 2;
    float o[64];
    float inv0, inv1;
#pragma unroll 1
    for (int hh = 0; hh < 2; hh++) {
        att_head(p, c, r, q, nt, row_base, hp * 2 + hh, o, inv0, inv1);
        if (hh == 0) {
#pragma unroll
            for (int i = 0; i < 8; i++)
                asm volatile("ld.shared.v4.b32 {%0, %1, %2, %3}, [%4];"
                             : "=r"(q[4 * i]), "=r"(q[4 * i + 1]), "=r"(q[4 * i + 2]), "=r"(q[4 * i + 3]) : "r"(stash + i * 2048) : "memory");
        } else {
            if ((tid & 127) == 0) bulk_wait_read<0>();
        }
        named_bar_sync(1 + wg, 128);
        att_store(p, c, o, inv0, inv1, row_base, hp * 2 + hh);
        PROF_STAMP(2, (jb >= 4 ? 2 : 5) + hh);
    }
}

template<int PHASE>
__global__ void __cluster_dims__(2, 1, 1) __launch_bounds__(NTHREADS, 1) main_kernel(const __grid_constant__ Params p) {
    extern __shared__ __align__(1024) uint8_t smem_raw[];
    Ctx c;
    c.sbase = (smem_u32(smem_raw) + 1023) & ~1023u;
    c.full0 = c.sbase + BAR_OFF;
    c.empty0 = c.full0 + 64;
    c.rank = cluster_rank();
    c.empty_rel = mapa_u32(c.empty0, (threadIdx.x & 1) ? (c.rank ^ 1) : c.rank);
    const int tid = threadIdx.x;
    c.wg = __shfl_sync(0xffffffffu, tid >> 7, 0);
    if (tid == 0) {
        for (int i = 0; i < NSLOT; i++) { mbar_init(c.full0 + 8 * i, 1); mbar_init(c.empty0 + 8 * i, 16); }
        asm volatile("fence.mbarrier_init.release.cluster;" ::: "memory");
    }
    if (tid >= 64 && tid < 128) {
        const int w = tid - 64;
        asm volatile("st.shared.b32 [%0], %1;" :: "r"(c.sbase + ONES_OFF + w * 4), "r"((w < 32 && (w & 3) == 0) ? 0x0000bf80u : 0u) : "memory");
    }
    fence_async_smem();
    __syncthreads();
    cluster_sync_all();
    const int cid = blockIdx.x >> 1;
    Ring r; r.idx = 0; r.phase = 0;

    if (c.wg == 2) {
        reg_dealloc<24>();
        if (tid == 256) {
            if (PHASE == 1) {
                if (cid < 48) {
                    int mp = cid / 6, sub = cid % 6;
                    int t0 = sub * 21 + (sub < 2 ? sub : 2), t1 = t0 + (sub < 2 ? 22 : 21);
                    kv_producer(p, c, r, mp * 2 + c.rank, t0, t1);
                } else {
                    int id = cid - 48;
                    b1_producer(p, c, r, (id >> 1) * 2 + c.rank, id & 1);
                }
            } else if (PHASE == 2) {
                int hp = cid & 15, j = cid >> 4;
                att_producer(p, c, r, 7 - j, hp);
                att_producer(p, c, r, j, hp);
            } else {
                int kq = cid & 3, nh = (cid >> 2) & 1, mp = cid >> 3;
                p3_producer(p, c, r, mp * 2 + c.rank, nh, kq);
            }
        }
        __syncwarp();
        cluster_sync_all();
    } else {
        reg_alloc<240>();
        PROF_STAMP(PHASE, 0);
        if (PHASE == 1) {
            if (cid < 48) {
                int mp = cid / 6, sub = cid % 6;
                int t0 = sub * 21 + (sub < 2 ? sub : 2), t1 = t0 + (sub < 2 ? 22 : 21);
                kv_consumer(p, c, r, mp * 2 + c.rank, t0, t1);
            } else {
                int id = cid - 48;
                b1_consumer(p, c, r, (id >> 1) * 2 + c.rank, id & 1);
            }
        } else if (PHASE == 2) {
            int hp = cid & 15, j = cid >> 4;
#pragma unroll 1
            for (int b = 0; b < 2; b++) att_consumer(p, c, r, b == 0 ? 7 - j : j, hp);
            if ((tid & 127) == 0) bulk_wait<0>();
        } else {
            int kq = cid & 3, nh = (cid >> 2) & 1, mp = cid >> 3;
            p3_consumer(p, c, r, mp * 2 + c.rank, nh, kq);
        }
        PROF_STAMP(PHASE, 15);
        cluster_sync_all();
    }
}

__device__ __forceinline__ float warp_sum(float v) {
#pragma unroll
    for (int o = 16; o > 0; o >>= 1) v += __shfl_xor_sync(0xffffffffu, v, o);
    return v;
}
__device__ __forceinline__ void ln_row(float (&v)[20]) {
    float s = 0.f;
#pragma unroll
    for (int i = 0; i < 20; i++) s += v[i];
    float mean = warp_sum(s) * (1.0f / DM);
    float q = 0.f;
#pragma unroll
    for (int i = 0; i < 20; i++) { float d = v[i] - mean; q = fmaf(d, d, q); }
    float var = bf16r(warp_sum(q) * (1.0f / DM));
    float mb = bf16r(mean);
    float den = bf16r(sqrtf(bf16r(var + 1e-5f)));
#pragma unroll
    for (int i = 0; i < 20; i++) v[i] = bf16r(__fdiv_rn(bf16r(v[i] - mb), den));
}
__global__ void __launch_bounds__(256) ln_kernel(const bf16* __restrict__ x, const bf16* __restrict__ b2) {
    const int row = blockIdx.x * 8 + (threadIdx.x >> 5), lane = threadIdx.x & 31;
    const uint2* xr = (const uint2*)(x + (size_t)row * DM);
    float v[20];
#pragma unroll
    for (int i = 0; i < 5; i++) {
        uint2 u = xr[lane + 32 * i];
        v[4 * i + 0] = __uint_as_float(u.x << 16); v[4 * i + 1] = __uint_as_float(u.x & 0xffff0000u);
        v[4 * i + 2] = __uint_as_float(u.y << 16); v[4 * i + 3] = __uint_as_float(u.y & 0xffff0000u);
    }
    float bb = __bfloat162float(b2[row]);
    float4* ar = (float4*)(g_acc + (size_t)row * DM);
#pragma unroll
    for (int i = 0; i < 5; i++) ar[lane + 32 * i] = make_float4(v[4 * i] + bb, v[4 * i + 1] + bb, v[4 * i + 2] + bb, v[4 * i + 3] + bb);
    ln_row(v);
    uint2* o = (uint2*)(g_xn + (size_t)row * DM);
#pragma unroll
    for (int i = 0; i < 5; i++) o[lane + 32 * i] = make_uint2(pack_bf16(v[4 * i], v[4 * i + 1]), pack_bf16(v[4 * i + 2], v[4 * i + 3]));
    ln_row(v);
    o = (uint2*)(g_h + (size_t)row * DM);
#pragma unroll
    for (int i = 0; i < 5; i++) o[lane + 32 * i] = make_uint2(pack_bf16(v[4 * i], v[4 * i + 1]), pack_bf16(v[4 * i + 2], v[4 * i + 3]));
}
__global__ void __launch_bounds__(256) fin_kernel(bf16* __restrict__ out) {
    int i = blockIdx.x * 256 + threadIdx.x;
    const float4* a = (const float4*)g_acc + 2 * i;
    float4 u = a[0], w = a[1];
    ((uint4*)out)[i] = make_uint4(pack_bf16(u.x, u.y), pack_bf16(u.z, u.w), pack_bf16(w.x, w.y), pack_bf16(w.z, w.w));
}

typedef CUresult (*PFN_encodeTiled)(CUtensorMap*, CUtensorMapDataType, cuuint32_t, void*, const cuuint64_t*, const cuuint64_t*,
                                    const cuuint32_t*, const cuuint32_t*, CUtensorMapInterleave, CUtensorMapSwizzle,
                                    CUtensorMapL2promotion, CUtensorMapFloatOOBfill);

static void make_map(PFN_encodeTiled enc, CUtensorMap* m, const void* ptr, uint64_t rows, uint64_t cols, uint32_t box_rows) {
    cuuint64_t dims[2] = {cols, rows};
    cuuint64_t strides[1] = {cols * 2};
    cuuint32_t box[2] = {64, box_rows};
    cuuint32_t es[2] = {1, 1};
    enc(m, CU_TENSOR_MAP_DATA_TYPE_BFLOAT16, 2, (void*)ptr, dims, strides, box, es, CU_TENSOR_MAP_INTERLEAVE_NONE,
        CU_TENSOR_MAP_SWIZZLE_128B, CU_TENSOR_MAP_L2_PROMOTION_L2_128B, CU_TENSOR_MAP_FLOAT_OOB_FILL_NONE);
}

extern "C" void kernel_launch(void* const* d_in, const int* in_sizes, int n_in, void* d_out, int out_size) {
    const bf16* x   = (const bf16*)d_in[0];
    const bf16* ckv = (const bf16*)d_in[1];
    const bf16* wq  = (const bf16*)d_in[2];
    const bf16* wuk = (const bf16*)d_in[3];
    const bf16* wuv = (const bf16*)d_in[4];
    const bf16* wo  = (const bf16*)d_in[5];
    const bf16* w1  = (const bf16*)d_in[7];
    const bf16* b1  = (const bf16*)d_in[8];
    const bf16* w2  = (const bf16*)d_in[9];
    const bf16* b2  = (const bf16*)d_in[10];

    static PFN_encodeTiled enc = nullptr;
    static void *p_xn, *p_h, *p_kv, *p_ctx, *p_uT;
    if (!enc) {
        void* fn = nullptr;
        cudaDriverEntryPointQueryResult st;
        cudaGetDriverEntryPoint("cuTensorMapEncodeTiled", &fn, cudaEnableDefault, &st);
        enc = (PFN_encodeTiled)fn;
        cudaGetSymbolAddress(&p_xn, g_xn);
        cudaGetSymbolAddress(&p_h, g_h);
        cudaGetSymbolAddress(&p_kv, g_kv);
        cudaGetSymbolAddress(&p_ctx, g_ctx);
        cudaGetSymbolAddress(&p_uT, g_uT);
        cudaFuncSetAttribute(main_kernel<1>, cudaFuncAttributeMaxDynamicSharedMemorySize, SMEM_BYTES);
        cudaFuncSetAttribute(main_kernel<2>, cudaFuncAttributeMaxDynamicSharedMemorySize, SMEM_BYTES);
        cudaFuncSetAttribute(main_kernel<3>, cudaFuncAttributeMaxDynamicSharedMemorySize, SMEM_BYTES);
    }
    Params p;
    make_map(enc, &p.ckv, ckv, SEQ, DC, 128);
    make_map(enc, &p.wuk, wuk, DC, NH * HD, 128);
    make_map(enc, &p.wuv, wuv, DC, NH * HD, 128);
    make_map(enc, &p.kv_st, p_kv, 64 * SEQ, HD, 64);
    make_map(enc, &p.kv_ld, p_kv, 64 * SEQ, HD, 128);
    make_map(enc, &p.xn, p_xn, SEQ, DM, 64);
    make_map(enc, &p.wq, wq, DM, NH * HD, 64);
    make_map(enc, &p.ctx_st, p_ctx, SEQ, NH * HD, 64);
    make_map(enc, &p.ctx_ld, p_ctx, SEQ, NH * HD, 128);
    make_map(enc, &p.wo, wo, NH * HD, DM, 64);
    make_map(enc, &p.w2, w2, FF, SEQ, 64);
    make_map(enc, &p.uT, p_uT, FF, DM, 64);
    make_map(enc, &p.w1, w1, SEQ, FF, 64);
    make_map(enc, &p.h, p_h, SEQ, DM, 64);
    p.b1 = b1;

    cudaStream_t st = cudaStreamPerThread;
    ln_kernel<<<SEQ / 8, 256, 0, st>>>(x, b2);
    main_kernel<1><<<124, NTHREADS, SMEM_BYTES, st>>>(p);
    main_kernel<2><<<128, NTHREADS, SMEM_BYTES, st>>>(p);
    main_kernel<3><<<128, NTHREADS, SMEM_BYTES, st>>>(p);
    fin_kernel<<<SEQ * DM / 8 / 256, 256, 0, st>>>((bf16*)d_out);
}
```

```cpp
#include <cuda_runtime.h>
#include <cuda_bf16.h>
#include <cuda.h>
#include <stdint.h>

typedef __nv_bfloat16 bf16;

constexpr int SEQ = 2048;
constexpr int DM  = 640;
constexpr int DC  = 512;
constexpr int NH  = 32;
constexpr int HD  = 128;
constexpr int FF  = 1728;

__device__ __align__(1024) bf16  g_xn[SEQ * DM];
__device__ __align__(1024) bf16  g_h[SEQ * DM];
__device__ __align__(1024) bf16  g_kv[64 * SEQ * HD];
__device__ __align__(1024) bf16  g_ctx[SEQ * NH * HD];
__device__ __align__(1024) bf16  g_uT[FF * DM];
__device__ int g_abort = 0;

__device__ __forceinline__ uint32_t smem_u32(const void* p) { return (uint32_t)__cvta_generic_to_shared(p); }
__device__ __forceinline__ void mbar_init(uint32_t bar, uint32_t count) {
    asm volatile("mbarrier.init.shared::cta.b64 [%0], %1;" :: "r"(bar), "r"(count) : "memory");
}
__device__ __forceinline__ void mbar_expect_tx(uint32_t bar, uint32_t bytes) {
    asm volatile("mbarrier.arrive.expect_tx.shared::cta.b64 _, [%0], %1;" :: "r"(bar), "r"(bytes) : "memory");
}
__device__ __forceinline__ void mbar_arrive(uint32_t bar) {
    asm volatile("mbarrier.arrive.shared::cta.b64 _, [%0];" :: "r"(bar) : "memory");
}
__device__ __forceinline__ void mbar_arrive_if(uint32_t bar, uint32_t pred) {
    asm volatile("{\n.reg .pred p;\nsetp.ne.u32 p, %1, 0;\n@p mbarrier.arrive.shared::cta.b64 _, [%0];\n}\n" :: "r"(bar), "r"(pred) : "memory");
}
__device__ __forceinline__ void mbar_arrive_cluster_if(uint32_t bar, uint32_t pred) {
    asm volatile("{\n.reg .pred p;\nsetp.ne.u32 p, %1, 0;\n@p mbarrier.arrive.shared::cluster.b64 _, [%0];\n}\n" :: "r"(bar), "r"(pred) : "memory");
}
__device__ __forceinline__ bool mbar_try_wait(uint32_t bar, uint32_t parity) {
    uint32_t ok;
    asm volatile("{\n.reg .pred p;\nmbarrier.try_wait.parity.shared::cta.b64 p, [%1], %2;\nselp.u32 %0, 1, 0, p;\n}\n"
                 : "=r"(ok) : "r"(bar), "r"(parity) : "memory");
    return ok != 0;
}
__device__ __forceinline__ void mbar_wait(uint32_t bar, uint32_t parity) {
    asm volatile("{\n.reg .pred p;\n.reg .u32 n;\n"
                 "mov.u32 n, 0;\n"
                 "MBW_LOOP:\n"
                 "mbarrier.try_wait.parity.shared::cta.b64 p, [%0], %1;\n"
                 "@p bra MBW_DONE;\n"
                 "add.u32 n, n, 1;\n"
                 "setp.lt.u32 p, n, 0x400000;\n"
                 "@p bra MBW_LOOP;\n"
                 "MBW_DONE:\n}\n" :: "r"(bar), "r"(parity) : "memory");
}
__device__ __forceinline__ bool mbar_wait_lazy(uint32_t bar, uint32_t parity) {
    uint32_t spins = 0;
    while (!mbar_try_wait(bar, parity)) {
        __nanosleep(250);
        if ((++spins & 0xffu) == 0) {
            if (spins > (1u << 22)) g_abort = 1;
            if (*(volatile int*)&g_abort) return false;
        }
    }
    return true;
}
__device__ __forceinline__ uint32_t mapa_u32(uint32_t addr, uint32_t rank) {
    uint32_t r;
    asm volatile("mapa.shared::cluster.u32 %0, %1, %2;" : "=r"(r) : "r"(addr), "r"(rank));
    return r;
}
__device__ __forceinline__ uint32_t cluster_rank() {
    uint32_t r;
    asm volatile("mov.u32 %0, %%cluster_ctarank;" : "=r"(r));
    return r;
}
__device__ __forceinline__ void cluster_sync_all() {
    asm volatile("barrier.cluster.arrive.release.aligned;\nbarrier.cluster.wait.acquire.aligned;" ::: "memory");
}
__device__ __forceinline__ void tma_load(uint32_t dst, const CUtensorMap* map, int c0, int c1, uint32_t bar) {
    asm volatile("cp.async.bulk.tensor.2d.shared::cluster.global.mbarrier::complete_tx::bytes [%0], [%1, {%3, %4}], [%2];"
                 :: "r"(dst), "l"((uint64_t)map), "r"(bar), "r"(c0), "r"(c1) : "memory");
}
__device__ __forceinline__ void tma_load_mc(uint32_t dst, const CUtensorMap* map, int c0, int c1, uint32_t bar) {
    asm volatile("cp.async.bulk.tensor.2d.shared::cluster.global.mbarrier::complete_tx::bytes.multicast::cluster [%0], [%1, {%3, %4}], [%2], %5;"
                 :: "r"(dst), "l"((uint64_t)map), "r"(bar), "r"(c0), "r"(c1), "h"((uint16_t)3) : "memory");
}
__device__ __forceinline__ void tma_store(const CUtensorMap* map, uint32_t src, int c0, int c1) {
    asm volatile("cp.async.bulk.tensor.2d.global.shared::cta.bulk_group [%0, {%2, %3}], [%1];"
                 :: "l"((uint64_t)map), "r"(src), "r"(c0), "r"(c1) : "memory");
}
__device__ __forceinline__ void bulk_commit() { asm volatile("cp.async.bulk.commit_group;" ::: "memory"); }
template<int N> __device__ __forceinline__ void bulk_wait_read() { asm volatile("cp.async.bulk.wait_group.read %0;" :: "n"(N) : "memory"); }
template<int N> __device__ __forceinline__ void bulk_wait() { asm volatile("cp.async.bulk.wait_group %0;" :: "n"(N) : "memory"); }
__device__ __forceinline__ void fence_async_smem() { asm volatile("fence.proxy.async.shared::cta;" ::: "memory"); }
__device__ __forceinline__ void prefetch_tmap(const CUtensorMap* map) {
    asm volatile("prefetch.tensormap [%0];" :: "l"((uint64_t)map) : "memory");
}
__device__ __forceinline__ void named_bar_sync(int id, int n) { asm volatile("bar.sync %0, %1;" :: "r"(id), "r"(n) : "memory"); }

__device__ __forceinline__ void ldmatrix_x4(uint32_t& r0, uint32_t& r1, uint32_t& r2, uint32_t& r3, uint32_t addr) {
    asm volatile("ldmatrix.sync.aligned.m8n8.x4.shared.b16 {%0, %1, %2, %3}, [%4];"
                 : "=r"(r0), "=r"(r1), "=r"(r2), "=r"(r3) : "r"(addr) : "memory");
}
__device__ __forceinline__ void stmatrix_x4(uint32_t addr, uint32_t r0, uint32_t r1, uint32_t r2, uint32_t r3) {
    asm volatile("stmatrix.sync.aligned.m8n8.x4.shared.b16 [%0], {%1, %2, %3, %4};"
                 :: "r"(addr), "r"(r0), "r"(r1), "r"(r2), "r"(r3) : "memory");
}
__device__ __forceinline__ uint32_t pack_bf16(float lo, float hi) {
    uint32_t r;
    asm("cvt.rn.bf16x2.f32 %0, %1, %2;" : "=r"(r) : "f"(hi), "f"(lo));
    return r;
}
__device__ __forceinline__ float ex2(float x) {
    float y;
    asm("ex2.approx.ftz.f32 %0, %1;" : "=f"(y) : "f"(x));
    return y;
}
__device__ __forceinline__ float bf16r(float x) { return __bfloat162float(__float2bfloat16_rn(x)); }

__device__ __forceinline__ uint64_t make_desc(uint32_t addr, uint32_t lbo, uint32_t sbo) {
    return (uint64_t)((addr & 0x3FFFF) >> 4) | ((uint64_t)(lbo >> 4) << 16) | ((uint64_t)(sbo >> 4) << 32) | (1ull << 62);
}
__device__ __forceinline__ void wg_fence() { asm volatile("wgmma.fence.sync.aligned;" ::: "memory"); }
__device__ __forceinline__ void wg_commit() { asm volatile("wgmma.commit_group.sync.aligned;" ::: "memory"); }
template<int N> __device__ __forceinline__ void wg_wait() { asm volatile("wgmma.wait_group.sync.aligned %0;" :: "n"(N) : "memory"); }
template<int R> __device__ __forceinline__ void reg_alloc() { asm volatile("setmaxnreg.inc.sync.aligned.u32 %0;" :: "n"(R)); }
template<int R> __device__ __forceinline__ void reg_dealloc() { asm volatile("setmaxnreg.dec.sync.aligned.u32 %0;" :: "n"(R)); }
template<int N> __device__ __forceinline__ void fence_regs(float (&d)[N]) {
#pragma unroll
    for (int i = 0; i < N; i++) asm volatile("" : "+f"(d[i]) :: "memory");
}
template<int N> __device__ __forceinline__ void fence_regs_u(uint32_t (&d)[N]) {
#pragma unroll
    for (int i = 0; i < N; i++) asm volatile("" : "+r"(d[i]) :: "memory");
}

template<int TB>
__device__ __forceinline__ void wgmma_m64n64k16_rs(float (&d)[32], uint32_t a0, uint32_t a1, uint32_t a2, uint32_t a3, uint64_t db, int scale_d) {
    asm volatile("{\n.reg .pred p;\n"
        "setp.ne.b32 p, %37, 0;\n"
        "wgmma.mma_async.sync.aligned.m64n64k16.f32.bf16.bf16 "
        "{%0, %1, %2, %3, %4, %5, %6, %7, %8, %9, %10, %11, %12, %13, %14, %15, %16, %17, %18, %19, %20, %21, %22, %23, %24, %25, %26, %27, %28, %29, %30, %31}, "
        "{%32, %33, %34, %35}, %36, p, 1, 1, %38;\n}\n"
        : "+f"(d[0]), "+f"(d[1]), "+f"(d[2]), "+f"(d[3]), "+f"(d[4]), "+f"(d[5]), "+f"(d[6]), "+f"(d[7]), "+f"(d[8]), "+f"(d[9]), "+f"(d[10]), "+f"(d[11]), "+f"(d[12]), "+f"(d[13]), "+f"(d[14]), "+f"(d[15]), "+f"(d[16]), "+f"(d[17]), "+f"(d[18]), "+f"(d[19]), "+f"(d[20]), "+f"(d[21]), "+f"(d[22]), "+f"(d[23]), "+f"(d[24]), "+f"(d[25]), "+f"(d[26]), "+f"(d[27]), "+f"(d[28]), "+f"(d[29]), "+f"(d[30]), "+f"(d[31])
        : "r"(a0), "r"(a1), "r"(a2), "r"(a3), "l"(db), "r"(scale_d), "n"(TB));
}
template<int TB>
__device__ __forceinline__ void wgmma_m64n128k16_rs(float (&d)[64], uint32_t a0, uint32_t a1, uint32_t a2, uint32_t a3, uint64_t db, int scale_d) {
    asm volatile("{\n.reg .pred p;\n"
        "setp.ne.b32 p, %69, 0;\n"
        "wgmma.mma_async.sync.aligned.m64n128k16.f32.bf16.bf16 "
        "{%0, %1, %2, %3, %4, %5, %6, %7, %8, %9, %10, %11, %12, %13, %14, %15, %16, %17, %18, %19, %20, %21, %22, %23, %24, %25, %26, %27, %28, %29, %30, %31, %32, %33, %34, %35, %36, %37, %38, %39, %40, %41, %42, %43, %44, %45, %46, %47, %48, %49, %50, %51, %52, %53, %54, %55, %56, %57, %58, %59, %60, %61, %62, %63}, "
        "{%64, %65, %66, %67}, %68, p, 1, 1, %70;\n}\n"
        : "+f"(d[0]), "+f"(d[1]), "+f"(d[2]), "+f"(d[3]), "+f"(d[4]), "+f"(d[5]), "+f"(d[6]), "+f"(d[7]), "+f"(d[8]), "+f"(d[9]), "+f"(d[10]), "+f"(d[11]), "+f"(d[12]), "+f"(d[13]), "+f"(d[14]), "+f"(d[15]), "+f"(d[16]), "+f"(d[17]), "+f"(d[18]), "+f"(d[19]), "+f"(d[20]), "+f"(d[21]), "+f"(d[22]), "+f"(d[23]), "+f"(d[24]), "+f"(d[25]), "+f"(d[26]), "+f"(d[27]), "+f"(d[28]), "+f"(d[29]), "+f"(d[30]), "+f"(d[31]), "+f"(d[32]), "+f"(d[33]), "+f"(d[34]), "+f"(d[35]), "+f"(d[36]), "+f"(d[37]), "+f"(d[38]), "+f"(d[39]), "+f"(d[40]), "+f"(d[41]), "+f"(d[42]), "+f"(d[43]), "+f"(d[44]), "+f"(d[45]), "+f"(d[46]), "+f"(d[47]), "+f"(d[48]), "+f"(d[49]), "+f"(d[50]), "+f"(d[51]), "+f"(d[52]), "+f"(d[53]), "+f"(d[54]), "+f"(d[55]), "+f"(d[56]), "+f"(d[57]), "+f"(d[58]), "+f"(d[59]), "+f"(d[60]), "+f"(d[61]), "+f"(d[62]), "+f"(d[63])
        : "r"(a0), "r"(a1), "r"(a2), "r"(a3), "l"(db), "r"(scale_d), "n"(TB));
}
template<int TA, int TB>
__device__ __forceinline__ void wgmma_m64n128k16_ss(float (&d)[64], uint64_t da, uint64_t db, int scale_d) {
    asm volatile("{\n.reg .pred p;\n"
        "setp.ne.b32 p, %66, 0;\n"
        "wgmma.mma_async.sync.aligned.m64n128k16.f32.bf16.bf16 "
        "{%0, %1, %2, %3, %4, %5, %6, %7, %8, %9, %10, %11, %12, %13, %14, %15, %16, %17, %18, %19, %20, %21, %22, %23, %24, %25, %26, %27, %28, %29, %30, %31, %32, %33, %34, %35, %36, %37, %38, %39, %40, %41, %42, %43, %44, %45, %46, %47, %48, %49, %50, %51, %52, %53, %54, %55, %56, %57, %58, %59, %60, %61, %62, %63}, "
        "%64, %65, p, 1, 1, %67, %68;\n}\n"
        : "+f"(d[0]), "+f"(d[1]), "+f"(d[2]), "+f"(d[3]), "+f"(d[4]), "+f"(d[5]), "+f"(d[6]), "+f"(d[7]), "+f"(d[8]), "+f"(d[9]), "+f"(d[10]), "+f"(d[11]), "+f"(d[12]), "+f"(d[13]), "+f"(d[14]), "+f"(d[15]), "+f"(d[16]), "+f"(d[17]), "+f"(d[18]), "+f"(d[19]), "+f"(d[20]), "+f"(d[21]), "+f"(d[22]), "+f"(d[23]), "+f"(d[24]), "+f"(d[25]), "+f"(d[26]), "+f"(d[27]), "+f"(d[28]), "+f"(d[29]), "+f"(d[30]), "+f"(d[31]), "+f"(d[32]), "+f"(d[33]), "+f"(d[34]), "+f"(d[35]), "+f"(d[36]), "+f"(d[37]), "+f"(d[38]), "+f"(d[39]), "+f"(d[40]), "+f"(d[41]), "+f"(d[42]), "+f"(d[43]), "+f"(d[44]), "+f"(d[45]), "+f"(d[46]), "+f"(d[47]), "+f"(d[48]), "+f"(d[49]), "+f"(d[50]), "+f"(d[51]), "+f"(d[52]), "+f"(d[53]), "+f"(d[54]), "+f"(d[55]), "+f"(d[56]), "+f"(d[57]), "+f"(d[58]), "+f"(d[59]), "+f"(d[60]), "+f"(d[61]), "+f"(d[62]), "+f"(d[63])
        : "l"(da), "l"(db), "r"(scale_d), "n"(TA), "n"(TB));
}
template<int TA, int TB>
__device__ __forceinline__ void wgmma_m64n192k16_ss(float (&d)[96], uint64_t da, uint64_t db, int scale_d) {
    asm volatile("{\n.reg .pred p;\n"
        "setp.ne.b32 p, %98, 0;\n"
        "wgmma.mma_async.sync.aligned.m64n192k16.f32.bf16.bf16 "
        "{%0, %1, %2, %3, %4, %5, %6, %7, %8, %9, %10, %11, %12, %13, %14, %15, %16, %17, %18, %19, %20, %21, %22, %23, %24, %25, %26, %27, %28, %29, %30, %31, %32, %33, %34, %35, %36, %37, %38, %39, %40, %41, %42, %43, %44, %45, %46, %47, %48, %49, %50, %51, %52, %53, %54, %55, %56, %57, %58, %59, %60, %61, %62, %63, %64, %65, %66, %67, %68, %69, %70, %71, %72, %73, %74, %75, %76, %77, %78, %79, %80, %81, %82, %83, %84, %85, %86, %87, %88, %89, %90, %91, %92, %93, %94, %95}, "
        "%96, %97, p, 1, 1, %99, %100;\n}\n"
        : "+f"(d[0]), "+f"(d[1]), "+f"(d[2]), "+f"(d[3]), "+f"(d[4]), "+f"(d[5]), "+f"(d[6]), "+f"(d[7]), "+f"(d[8]), "+f"(d[9]), "+f"(d[10]), "+f"(d[11]), "+f"(d[12]), "+f"(d[13]), "+f"(d[14]), "+f"(d[15]), "+f"(d[16]), "+f"(d[17]), "+f"(d[18]), "+f"(d[19]), "+f"(d[20]), "+f"(d[21]), "+f"(d[22]), "+f"(d[23]), "+f"(d[24]), "+f"(d[25]), "+f"(d[26]), "+f"(d[27]), "+f"(d[28]), "+f"(d[29]), "+f"(d[30]), "+f"(d[31]), "+f"(d[32]), "+f"(d[33]), "+f"(d[34]), "+f"(d[35]), "+f"(d[36]), "+f"(d[37]), "+f"(d[38]), "+f"(d[39]), "+f"(d[40]), "+f"(d[41]), "+f"(d[42]), "+f"(d[43]), "+f"(d[44]), "+f"(d[45]), "+f"(d[46]), "+f"(d[47]), "+f"(d[48]), "+f"(d[49]), "+f"(d[50]), "+f"(d[51]), "+f"(d[52]), "+f"(d[53]), "+f"(d[54]), "+f"(d[55]), "+f"(d[56]), "+f"(d[57]), "+f"(d[58]), "+f"(d[59]), "+f"(d[60]), "+f"(d[61]), "+f"(d[62]), "+f"(d[63]), "+f"(d[64]), "+f"(d[65]), "+f"(d[66]), "+f"(d[67]), "+f"(d[68]), "+f"(d[69]), "+f"(d[70]), "+f"(d[71]), "+f"(d[72]), "+f"(d[73]), "+f"(d[74]), "+f"(d[75]), "+f"(d[76]), "+f"(d[77]), "+f"(d[78]), "+f"(d[79]), "+f"(d[80]), "+f"(d[81]), "+f"(d[82]), "+f"(d[83]), "+f"(d[84]), "+f"(d[85]), "+f"(d[86]), "+f"(d[87]), "+f"(d[88]), "+f"(d[89]), "+f"(d[90]), "+f"(d[91]), "+f"(d[92]), "+f"(d[93]), "+f"(d[94]), "+f"(d[95])
        : "l"(da), "l"(db), "r"(scale_d), "n"(TA), "n"(TB));
}
template<int TA, int TB>
__device__ __forceinline__ void wgmma_m64n256k16_ss(float (&d)[128], uint64_t da, uint64_t db, int scale_d) {
    asm volatile("{\n.reg .pred p;\n"
        "setp.ne.b32 p, %130, 0;\n"
        "wgmma.mma_async.sync.aligned.m64n256k16.f32.bf16.bf16 "
        "{%0, %1, %2, %3, %4, %5, %6, %7, %8, %9, %10, %11, %12, %13, %14, %15, %16, %17, %18, %19, %20, %21, %22, %23, %24, %25, %26, %27, %28, %29, %30, %31, %32, %33, %34, %35, %36, %37, %38, %39, %40, %41, %42, %43, %44, %45, %46, %47, %48, %49, %50, %51, %52, %53, %54, %55, %56, %57, %58, %59, %60, %61, %62, %63, %64, %65, %66, %67, %68, %69, %70, %71, %72, %73, %74, %75, %76, %77, %78, %79, %80, %81, %82, %83, %84, %85, %86, %87, %88, %89, %90, %91, %92, %93, %94, %95, %96, %97, %98, %99, %100, %101, %102, %103, %104, %105, %106, %107, %108, %109, %110, %111, %112, %113, %114, %115, %116, %117, %118, %119, %120, %121, %122, %123, %124, %125, %126, %127}, "
        "%128, %129, p, 1, 1, %131, %132;\n}\n"
        : "+f"(d[0]), "+f"(d[1]), "+f"(d[2]), "+f"(d[3]), "+f"(d[4]), "+f"(d[5]), "+f"(d[6]), "+f"(d[7]), "+f"(d[8]), "+f"(d[9]), "+f"(d[10]), "+f"(d[11]), "+f"(d[12]), "+f"(d[13]), "+f"(d[14]), "+f"(d[15]), "+f"(d[16]), "+f"(d[17]), "+f"(d[18]), "+f"(d[19]), "+f"(d[20]), "+f"(d[21]), "+f"(d[22]), "+f"(d[23]), "+f"(d[24]), "+f"(d[25]), "+f"(d[26]), "+f"(d[27]), "+f"(d[28]), "+f"(d[29]), "+f"(d[30]), "+f"(d[31]), "+f"(d[32]), "+f"(d[33]), "+f"(d[34]), "+f"(d[35]), "+f"(d[36]), "+f"(d[37]), "+f"(d[38]), "+f"(d[39]), "+f"(d[40]), "+f"(d[41]), "+f"(d[42]), "+f"(d[43]), "+f"(d[44]), "+f"(d[45]), "+f"(d[46]), "+f"(d[47]), "+f"(d[48]), "+f"(d[49]), "+f"(d[50]), "+f"(d[51]), "+f"(d[52]), "+f"(d[53]), "+f"(d[54]), "+f"(d[55]), "+f"(d[56]), "+f"(d[57]), "+f"(d[58]), "+f"(d[59]), "+f"(d[60]), "+f"(d[61]), "+f"(d[62]), "+f"(d[63]), "+f"(d[64]), "+f"(d[65]), "+f"(d[66]), "+f"(d[67]), "+f"(d[68]), "+f"(d[69]), "+f"(d[70]), "+f"(d[71]), "+f"(d[72]), "+f"(d[73]), "+f"(d[74]), "+f"(d[75]), "+f"(d[76]), "+f"(d[77]), "+f"(d[78]), "+f"(d[79]), "+f"(d[80]), "+f"(d[81]), "+f"(d[82]), "+f"(d[83]), "+f"(d[84]), "+f"(d[85]), "+f"(d[86]), "+f"(d[87]), "+f"(d[88]), "+f"(d[89]), "+f"(d[90]), "+f"(d[91]), "+f"(d[92]), "+f"(d[93]), "+f"(d[94]), "+f"(d[95]), "+f"(d[96]), "+f"(d[97]), "+f"(d[98]), "+f"(d[99]), "+f"(d[100]), "+f"(d[101]), "+f"(d[102]), "+f"(d[103]), "+f"(d[104]), "+f"(d[105]), "+f"(d[106]), "+f"(d[107]), "+f"(d[108]), "+f"(d[109]), "+f"(d[110]), "+f"(d[111]), "+f"(d[112]), "+f"(d[113]), "+f"(d[114]), "+f"(d[115]), "+f"(d[116]), "+f"(d[117]), "+f"(d[118]), "+f"(d[119]), "+f"(d[120]), "+f"(d[121]), "+f"(d[122]), "+f"(d[123]), "+f"(d[124]), "+f"(d[125]), "+f"(d[126]), "+f"(d[127])
        : "l"(da), "l"(db), "r"(scale_d), "n"(TA), "n"(TB));
}
template<int TB>
__device__ __forceinline__ void wgmma_m64n64k16_rs_z(float (&d)[32], uint32_t a0, uint32_t a1, uint32_t a2, uint32_t a3, uint64_t db) {
    asm volatile("{\n.reg .pred p;\n"
        "setp.ne.b32 p, 0, 0;\n"
        "wgmma.mma_async.sync.aligned.m64n64k16.f32.bf16.bf16 "
        "{%0, %1, %2, %3, %4, %5, %6, %7, %8, %9, %10, %11, %12, %13, %14, %15, %16, %17, %18, %19, %20, %21, %22, %23, %24, %25, %26, %27, %28, %29, %30, %31}, "
        "{%32, %33, %34, %35}, %36, p, 1, 1, %37;\n}\n"
        : "=f"(d[0]), "=f"(d[1]), "=f"(d[2]), "=f"(d[3]), "=f"(d[4]), "=f"(d[5]), "=f"(d[6]), "=f"(d[7]), "=f"(d[8]), "=f"(d[9]), "=f"(d[10]), "=f"(d[11]), "=f"(d[12]), "=f"(d[13]), "=f"(d[14]), "=f"(d[15]), "=f"(d[16]), "=f"(d[17]), "=f"(d[18]), "=f"(d[19]), "=f"(d[20]), "=f"(d[21]), "=f"(d[22]), "=f"(d[23]), "=f"(d[24]), "=f"(d[25]), "=f"(d[26]), "=f"(d[27]), "=f"(d[28]), "=f"(d[29]), "=f"(d[30]), "=f"(d[31])
        : "r"(a0), "r"(a1), "r"(a2), "r"(a3), "l"(db), "n"(TB));
}

constexpr int NSLOT      = 6;
constexpr int SLOT_BYTES = 32768;
constexpr int STG_OFF    = NSLOT * SLOT_BYTES;
constexpr int BAR_OFF    = STG_OFF + 32768;
constexpr int MBOX_OFF   = BAR_OFF + 512;
constexpr int SMEM_BYTES = BAR_OFF + 640 + 1024;
constexpr int NTHREADS   = 384;

struct Params {
    CUtensorMap ckv;
    CUtensorMap wuk;
    CUtensorMap wuv;
    CUtensorMap kv_st;
    CUtensorMap kv_ld;
    CUtensorMap xn;
    CUtensorMap wq;
    CUtensorMap ctx_st;
    CUtensorMap ctx_ld;
    CUtensorMap wo;
    CUtensorMap w2;
    CUtensorMap uT;
    CUtensorMap uT_st;
    CUtensorMap w1;
    CUtensorMap h;
    const bf16* b1;
    const bf16* b2;
    const bf16* x;
    bf16* out;
};

struct __align__(16) Flags {
    uint32_t ln;
    uint32_t pad0[7];
    uint32_t u[2];
    uint32_t pad1[6];
    uint32_t done;
    uint32_t pad2[7];
    uint32_t kv[64 * 8];
    uint32_t p3[32];
    uint32_t ctx[8 * 32];
};
__device__ Flags g_flags;
__device__ __align__(1024) uint4 g_qstash[128 * 2 * 2 * 8 * 128];
__device__ __align__(1024) uint4 g_part[32 * 4 * 4 * 5 * 256];

__device__ __forceinline__ void flag_wait(const uint32_t* f, uint32_t target) {
    uint32_t spins = 0;
    while (true) {
        uint32_t v;
        asm volatile("ld.acquire.gpu.global.u32 %0, [%1];" : "=r"(v) : "l"(f) : "memory");
        if (v >= target) break;
        __nanosleep(100);
        if ((++spins & 0xffu) == 0) {
            if (spins > (1u << 22)) g_abort = 1;
            if (*(volatile int*)&g_abort) break;
        }
    }
    asm volatile("fence.proxy.async;" ::: "memory");
}
__device__ __forceinline__ void flag_signal(uint32_t* f, uint32_t inc) {
    asm volatile("red.release.gpu.global.add.u32 [%0], %1;" :: "l"(f), "r"(inc) : "memory");
}
struct Ctx {
    uint32_t sbase;
    uint32_t empty_rel;
    uint32_t rank;
    int wg;
    uint32_t sk;
};
struct Ring {
    uint32_t idx, phase;
    __device__ __forceinline__ void adv() { if (++idx == NSLOT) { idx = 0; phase ^= 1; } }
    __device__ __forceinline__ void adv2() { idx += 2; if (idx >= NSLOT) { idx -= NSLOT; phase ^= 1; } }
};
__device__ __forceinline__ uint32_t slot_addr(const Ctx& c, uint32_t idx) { return c.sbase + idx * SLOT_BYTES; }
__device__ __forceinline__ void wait_full(const Ctx& c, const Ring& r) { mbar_wait((c.sbase + BAR_OFF) + 8 * r.idx, r.phase); }
__device__ __forceinline__ void release(const Ctx& c, uint32_t idx) {
    __syncwarp();
    mbar_arrive_cluster_if(c.empty_rel + 8 * idx, (threadIdx.x & 31) < 2);
}
__device__ __forceinline__ uint32_t st_full(const Ctx& c, int wg, uint32_t slot) { return (c.sbase + BAR_OFF) + 128 + (wg * 2 + slot) * 8; }
__device__ __forceinline__ uint32_t st_empty(const Ctx& c, int wg, uint32_t slot) { return (c.sbase + BAR_OFF) + 160 + (wg * 2 + slot) * 8; }
__device__ __forceinline__ void stage_acquire(const Ctx& c, bool both) {
    const uint32_t k = c.sk;
    if (k >= 2) mbar_wait(st_empty(c, c.wg, k & 1), ((k >> 1) - 1) & 1);
    if (both && k >= 1) mbar_wait(st_empty(c, c.wg, (k - 1) & 1), ((k - 1) >> 1) & 1);
}
__device__ __forceinline__ void stage_submit(Ctx& c, const CUtensorMap* map, int c0, int c1, uint32_t src, uint32_t nbox, uint32_t* flag, uint32_t inc = 1) {
    const uint32_t slot = c.sk & 1;
    fence_async_smem();
    const uint32_t mb = c.sbase + MBOX_OFF + (c.wg * 2 + slot) * 32;
    asm volatile("{\n.reg .pred p;\nsetp.eq.u32 p, %7, 0;\n"
                 "@p st.shared.v2.b64 [%0], {%1, %2};\n"
                 "@p st.shared.v4.b32 [%0 + 16], {%3, %4, %5, %6};\n}\n"
                 :: "r"(mb), "l"((uint64_t)map), "l"((uint64_t)flag), "r"(c0), "r"(c1), "r"(src), "r"(nbox | (inc << 8)), "r"(threadIdx.x & 127) : "memory");
    __syncwarp();
    mbar_arrive_if(st_full(c, c.wg, slot), (threadIdx.x & 31) == 0);
    c.sk++;
}
__device__ __forceinline__ void store_agent(const Ctx& c, int wg) {
    for (uint32_t k = 0;; k++) {
        const uint32_t slot = k & 1;
        if (!mbar_wait_lazy(st_full(c, wg, slot), (k >> 1) & 1)) break;
        const uint32_t mb = c.sbase + MBOX_OFF + (wg * 2 + slot) * 32;
        uint64_t map, flag;
        uint32_t c0, c1, src, nbox;
        asm volatile("ld.shared.v2.b64 {%0, %1}, [%2];" : "=l"(map), "=l"(flag) : "r"(mb) : "memory");
        asm volatile("ld.shared.v4.b32 {%0, %1, %2, %3}, [%4];" : "=r"(c0), "=r"(c1), "=r"(src), "=r"(nbox) : "r"(mb + 16) : "memory");
        const uint32_t inc = nbox >> 8;
        nbox &= 0xff;
        if (nbox == 0) break;
        if (nbox == 3) {
            mbar_arrive(st_empty(c, wg, slot));
            bulk_wait<0>();
            asm volatile("fence.acq_rel.gpu;" ::: "memory");
            for (uint32_t t = c0; t < c1; t++)
                asm volatile("red.relaxed.gpu.global.add.u32 [%0], 1;" :: "l"(&g_flags.kv[(t >> 1) * 8]) : "memory");
            continue;
        }
        tma_store((const CUtensorMap*)map, src, c0, c1);
        if (nbox > 1) tma_store((const CUtensorMap*)map, src + 8192, c0 + 64, c1);
        bulk_commit();
        bulk_wait_read<0>();
        mbar_arrive(st_empty(c, wg, slot));
        if (flag) {
            bulk_wait<0>();
            flag_signal((uint32_t*)flag, inc);
        }
    }
    bulk_wait<0>();
}
__device__ __forceinline__ uint32_t acquire(const Ctx& c, const Ring& r, uint32_t bytes) {
    mbar_wait((c.sbase + BAR_OFF + 64) + 8 * r.idx, r.phase ^ 1);
    mbar_expect_tx((c.sbase + BAR_OFF) + 8 * r.idx, bytes);
    return slot_addr(c, r.idx);
}

__device__ __forceinline__ void kv_producer(const Params& p, const Ctx& c, Ring& r, int m, int t0, int t1) {
    for (int ch = 0; ch < 4; ch++) {
        uint32_t s = acquire(c, r, 32768);
        uint32_t bar = (c.sbase + BAR_OFF) + 8 * r.idx;
        tma_load(s, &p.ckv, ch * 128, m * 128, bar);
        tma_load(s + 16384, &p.ckv, ch * 128 + 64, m * 128, bar);
        r.adv();
    }
    for (int t = t0; t < t1; t++) {
        const CUtensorMap* wm = (t < 64) ? &p.wuk : &p.wuv;
        int col = (t & 63) * 64;
        for (int half = 0; half < 2; half++) {
            uint32_t s = acquire(c, r, 32768);
            tma_load_mc(s + c.rank * 16384, wm, col, half * 256 + c.rank * 128, (c.sbase + BAR_OFF) + 8 * r.idx);
            r.adv();
        }
    }
}

__device__ __forceinline__ void kv_epilogue(const Params& p, Ctx& c, float (&acc)[32], int t, int m, int t0, int t1) {
    const int tid = threadIdx.x, wg = c.wg, warp = (tid >> 5) & 3, lane = tid & 31;
    const uint32_t stg = c.sbase + STG_OFF + wg * 16384 + (c.sk & 1) * 8192;
    const int mi = lane >> 3;
    const int row = warp * 16 + (lane & 7) + 8 * (mi & 1);
    stage_acquire(c, false);
#pragma unroll
    for (int jj = 0; jj < 4; jj++) {
        int chunk = 2 * jj + (mi >> 1);
        stmatrix_x4(stg + row * 128 + ((chunk ^ (row & 7)) << 4),
                    pack_bf16(acc[8 * jj + 0], acc[8 * jj + 1]), pack_bf16(acc[8 * jj + 2], acc[8 * jj + 3]),
                    pack_bf16(acc[8 * jj + 4], acc[8 * jj + 5]), pack_bf16(acc[8 * jj + 6], acc[8 * jj + 7]));
    }
    stage_submit(c, &p.kv_st, (t & 1) * 64, (t >> 1) * SEQ + m * 128 + wg * 64, stg, 1, nullptr);
}

__device__ __forceinline__ void kv_issue(Ctx& c, const Ring& r, float (&acc)[32], const uint32_t (&a)[128], const int half) {
    wait_full(c, r);
    uint32_t s = slot_addr(c, r.idx);
    wg_fence();
    if (half == 0) {
#pragma unroll
        for (int kk = 0; kk < 16; kk++) {
            if (kk == 0) wgmma_m64n64k16_rs_z<1>(acc, a[0], a[1], a[2], a[3], make_desc(s, 8192, 1024));
            else wgmma_m64n64k16_rs<1>(acc, a[4 * kk], a[4 * kk + 1], a[4 * kk + 2], a[4 * kk + 3], make_desc(s + kk * 2048, 8192, 1024), 1);
        }
    } else {
#pragma unroll
        for (int kk = 0; kk < 16; kk++)
            wgmma_m64n64k16_rs<1>(acc, a[64 + 4 * kk], a[64 + 4 * kk + 1], a[64 + 4 * kk + 2], a[64 + 4 * kk + 3], make_desc(s + kk * 2048, 8192, 1024), 1);
    }
    wg_commit();
}

__device__ __forceinline__ void kv_consumer(const Params& p, Ctx& c, Ring& r, int m, int t0, int t1) {
    const int tid = threadIdx.x, wg = c.wg, warp = (tid >> 5) & 3, lane = tid & 31;
    uint32_t a[128];
    {
        const int mi = lane >> 3;
        const int row = wg * 64 + warp * 16 + (lane & 7) + 8 * (mi & 1);
#pragma unroll
        for (int ch = 0; ch < 4; ch++) {
            wait_full(c, r);
            uint32_t s = slot_addr(c, r.idx);
#pragma unroll
            for (int b = 0; b < 2; b++)
#pragma unroll
                for (int kk = 0; kk < 4; kk++) {
                    int chunk = 2 * kk + (mi >> 1);
                    int i = (ch * 8 + b * 4 + kk) * 4;
                    ldmatrix_x4(a[i], a[i + 1], a[i + 2], a[i + 3], s + b * 16384 + row * 128 + ((chunk ^ (row & 7)) << 4));
                }
            release(c, r.idx);
            r.adv();
        }
    }
    float acc0[32], acc1[32];
    uint32_t prev = 0;
    int t = t0;
    kv_issue(c, r, acc0, a, 0); prev = r.idx; r.adv();
    kv_issue(c, r, acc0, a, 1);
    wg_wait<1>(); release(c, prev); prev = r.idx; r.adv();
    t++;
    while (true) {
        if (t >= t1) { wg_wait<0>(); fence_regs(acc0); release(c, prev); kv_epilogue(p, c, acc0, t - 1, m, t0, t1); break; }
        kv_issue(c, r, acc1, a, 0);
        wg_wait<1>(); fence_regs(acc0); release(c, prev); prev = r.idx; r.adv();
        kv_epilogue(p, c, acc0, t - 1, m, t0, t1);
        kv_issue(c, r, acc1, a, 1);
        wg_wait<1>(); release(c, prev); prev = r.idx; r.adv();
        t++;
        if (t >= t1) { wg_wait<0>(); fence_regs(acc1); release(c, prev); kv_epilogue(p, c, acc1, t - 1, m, t0, t1); break; }
        kv_issue(c, r, acc0, a, 0);
        wg_wait<1>(); fence_regs(acc1); release(c, prev); prev = r.idx; r.adv();
        kv_epilogue(p, c, acc1, t - 1, m, t0, t1);
        kv_issue(c, r, acc0, a, 1);
        wg_wait<1>(); release(c, prev); prev = r.idx; r.adv();
        t++;
    }
    stage_acquire(c, false);
    stage_submit(c, nullptr, t0, t1, m >> 1, 3, nullptr);
}

template<int AMODE>
__device__ __forceinline__ void g320_producer(const Ctx& c, Ring& r, const CUtensorMap* amap, int a_m0, int a_k0,
                                              const CUtensorMap* bmap, int b_n0, int b_k0, int nsteps) {
#pragma unroll 1
    for (int st = 0; st < nsteps; st++) {
        const uint32_t x = acquire(c, r, 28672);
        const uint32_t bx = (c.sbase + BAR_OFF) + 8 * r.idx;
        const int ka = a_k0 + st * 32, kb = b_k0 + st * 32;
        const uint32_t par = (st + c.rank) & 1;
        tma_load_mc(x + 8192 + par * 4096, bmap, b_n0 + par * 64, kb, bx);
        tma_load_mc(x + 16384 + par * 4096, bmap, b_n0 + 128 + par * 64, kb, bx);
        if (par == 0) tma_load_mc(x + 24576, bmap, b_n0 + 256, kb, bx);
        if (AMODE == 0) {
            tma_load(x, amap, ka, a_m0, bx);
        } else {
            tma_load(x, amap, a_m0, ka, bx);
            tma_load(x + 4096, amap, a_m0 + 64, ka, bx);
        }
        r.adv();
    }
}

template<int AMODE>
__device__ __forceinline__ void g320_segment(Ctx& c, Ring& r, float (&acc0)[64], float (&acc1)[96], int nsteps,
                                             int& first, uint32_t& prev) {
    const int wg = c.wg;
#pragma unroll 1
    for (int st = 0; st < nsteps; st++) {
        wait_full(c, r);
        const uint32_t x = slot_addr(c, r.idx);
        wg_fence();
#pragma unroll
        for (int kk = 0; kk < 2; kk++) {
            const uint64_t da = (AMODE == 0) ? ((make_desc(x + wg * 4096 + kk * 32, 16, 512) & ~(3ull << 62)) | (2ull << 62))
                                             : make_desc(x + wg * 4096 + kk * 2048, 4096, 1024);
            wgmma_m64n128k16_ss<AMODE, 1>(acc0, da, make_desc(x + 8192 + kk * 2048, 4096, 1024), 1);
            wgmma_m64n192k16_ss<AMODE, 1>(acc1, da, make_desc(x + 16384 + kk * 2048, 4096, 1024), 1);
        }
        wg_commit();
        if (!first) { wg_wait<1>(); release(c, prev); }
        first = 0;
        prev = r.idx;
        r.adv();
    }
}

__device__ __forceinline__ float gelu_tanh(float u) {
    const float k1 = -1.5957691216057308f * 1.4426950408889634f, k2 = k1 * 0.044715f;
    float e = ex2(u * fmaf(u * u, k2, k1));
    float r;
    asm("rcp.approx.ftz.f32 %0, %1;" : "=f"(r) : "f"(1.0f + e));
    return u * r;
}
__device__ __forceinline__ uint32_t b1_act(uint32_t v, float bias) {
    v = pack_bf16(__uint_as_float(v << 16) + bias, __uint_as_float(v & 0xffff0000u) + bias);
    return pack_bf16(gelu_tanh(__uint_as_float(v << 16)), gelu_tanh(__uint_as_float(v & 0xffff0000u)));
}

__device__ __forceinline__ void b1_producer(const Params& p, const Ctx& c, Ring& r, int m, int nh) {
    g320_producer<1>(c, r, &p.w1, m * 128, 0, &p.h, nh * 320, 0, 64);
}
template<int OFF, int N>
__device__ __forceinline__ void b1_stage(uint32_t dst, uint32_t sw, const float (&acc)[N]) {
#pragma unroll
    for (int jj = 0; jj < 4; jj++)
        stmatrix_x4(dst + (((2 * jj) ^ sw) << 4),
                    pack_bf16(acc[8 * (OFF + jj) + 0], acc[8 * (OFF + jj) + 1]), pack_bf16(acc[8 * (OFF + jj) + 2], acc[8 * (OFF + jj) + 3]),
                    pack_bf16(acc[8 * (OFF + jj) + 4], acc[8 * (OFF + jj) + 5]), pack_bf16(acc[8 * (OFF + jj) + 6], acc[8 * (OFF + jj) + 7]));
}
__device__ __forceinline__ void b1_consumer(const Params& p, Ctx& c, Ring& r, int m, int nh) {
    float acc0[64], acc1[96];
#pragma unroll
    for (int i = 0; i < 64; i++) acc0[i] = 0.f;
#pragma unroll
    for (int i = 0; i < 96; i++) acc1[i] = 0.f;
    int first = 1; uint32_t px = 0;
    const int row0 = m * 128 + c.wg * 64;
    uint32_t bias01, bias23;
    {
        const int rb = row0 + ((threadIdx.x >> 5) & 3) * 16 + ((threadIdx.x & 31) >> 3);
        const unsigned short* bp = (const unsigned short*)p.b1;
        bias01 = (uint32_t)bp[min(rb, FF - 1)] | ((uint32_t)bp[min(rb + 4, FF - 1)] << 16);
        bias23 = (uint32_t)bp[min(rb + 8, FF - 1)] | ((uint32_t)bp[min(rb + 12, FF - 1)] << 16);
    }
    g320_segment<1>(c, r, acc0, acc1, 64, first, px);
    wg_wait<0>(); fence_regs(acc0); fence_regs(acc1);
    release(c, px);
    const int tid = threadIdx.x, warp = (tid >> 5) & 3, lane = tid & 31;
    const int mi = lane >> 3;
    const int row = warp * 16 + (lane & 7) + 8 * (mi & 1);
    const uint32_t sw = (mi >> 1) ^ (row & 7);
#pragma unroll 1
    for (int b = 0; b < 5; b++) {
        const uint32_t stg = c.sbase + STG_OFF + c.wg * 16384 + (c.sk & 1) * 8192;
        stage_acquire(c, b == 0);
        const uint32_t dst = stg + row * 128;
        if (b == 0) b1_stage<0>(dst, sw, acc0);
        else if (b == 1) b1_stage<4>(dst, sw, acc0);
        else if (b == 2) b1_stage<0>(dst, sw, acc1);
        else if (b == 3) b1_stage<4>(dst, sw, acc1);
        else b1_stage<8>(dst, sw, acc1);
        __syncwarp();
#pragma unroll 1
        for (int it = 0; it < 4; it++) {
            const int rr = warp * 16 + it * 4 + (lane >> 3);
            const uint32_t a = stg + rr * 128 + (lane & 7) * 16;
            const uint32_t bw = (it & 2) ? bias23 : bias01;
            const float bias = __uint_as_float((it & 1) ? (bw & 0xffff0000u) : (bw << 16));
            uint32_t v0, v1, v2, v3;
            asm volatile("ld.shared.v4.b32 {%0, %1, %2, %3}, [%4];" : "=r"(v0), "=r"(v1), "=r"(v2), "=r"(v3) : "r"(a) : "memory");
            v0 = b1_act(v0, bias); v1 = b1_act(v1, bias); v2 = b1_act(v2, bias); v3 = b1_act(v3, bias);
            asm volatile("st.shared.v4.b32 [%0], {%1, %2, %3, %4};" :: "r"(a), "r"(v0), "r"(v1), "r"(v2), "r"(v3) : "memory");
        }
        stage_submit(c, &p.uT_st, nh * 320 + b * 64, row0, stg, 1, b == 4 ? &g_flags.u[nh] : nullptr);
    }
}

struct P3Plan { int a0, a1, c0, nc, b0, b1; };
__device__ __forceinline__ P3Plan p3_plan(int nh, int kq) {
    P3Plan q;
    q.b0 = 16 + 4 * kq; q.b1 = q.b0 + 4;
    if (nh == 0) {
        q.a0 = 4 * kq; q.a1 = q.a0 + 4;
        q.c0 = kq * 13 + (kq < 2 ? kq : 2); q.nc = kq < 2 ? 14 : 13;
    } else {
        q.a0 = kq < 3 ? 4 * kq + (kq > 0 ? 1 : 0) : 13; q.a1 = kq == 0 ? 5 : (kq < 3 ? q.a0 + 4 : 16);
        q.c0 = kq == 0 ? 0 : (kq == 1 ? 16 : 35); q.nc = kq == 0 ? 16 : (kq < 3 ? 19 : 0);
    }
    return q;
}
__device__ __forceinline__ void p3_producer(const Params& p, const Ctx& c, Ring& r, int m, int nh, int kq) {
    const P3Plan q = p3_plan(nh, kq);
#pragma unroll 1
    for (int seg = 0; seg < 3; seg++) {
        if (seg == 2) {
            if (q.nc > 0) {
                flag_wait(&g_flags.u[nh], 28);
                g320_producer<1>(c, r, &p.w2, m * 128, q.c0 * 32, &p.uT, nh * 320, q.c0 * 32, q.nc);
            }
        } else {
            const int h1 = seg == 0 ? q.a1 : q.b1;
#pragma unroll 1
            for (int hd = seg == 0 ? q.a0 : q.b0; hd < h1; hd++) {
                flag_wait(&g_flags.ctx[(m >> 1) * 32 + hd], 4);
                g320_producer<0>(c, r, &p.ctx_ld, m * 128, hd * 128, &p.wo, nh * 320, hd * 128, 4);
            }
        }
    }
}
__device__ __forceinline__ void p3_consumer(const Params& p, Ctx& c, Ring& r, int m, int nh, int kq) {
    const int tid = threadIdx.x, wg = c.wg, warp = (tid >> 5) & 3, lane = tid & 31;
    float acc0[64], acc1[96];
#pragma unroll
    for (int i = 0; i < 64; i++) acc0[i] = 0.f;
#pragma unroll
    for (int i = 0; i < 96; i++) acc1[i] = 0.f;
    int first = 1; uint32_t px = 0;
    const P3Plan q3 = p3_plan(nh, kq);
#pragma unroll 1
    for (int seg = 0; seg < 3; seg++) {
        if (seg == 2) g320_segment<1>(c, r, acc0, acc1, q3.nc, first, px);
        else g320_segment<0>(c, r, acc0, acc1, seg == 0 ? 4 * (q3.a1 - q3.a0) : 4 * (q3.b1 - q3.b0), first, px);
    }
    wg_wait<0>(); fence_regs(acc0); fence_regs(acc1);
    release(c, px);
    const int tile = m * 2 + nh;
    float own[40];
#pragma unroll
    for (int i = 0; i < 40; i++) own[i] = 0.f;
    uint4* dst = g_part + (size_t)((tile * 4 + kq) * 4) * 1280 + tid;
#pragma unroll
    for (int bp = 0; bp < 20; bp++) {
        const int q = bp / 5, i = bp % 5;
        float v[8];
#pragma unroll
        for (int e = 0; e < 8; e++) v[e] = (bp < 8) ? acc0[8 * bp + e] : acc1[8 * (bp - 8) + e];
        if (q != kq) {
            dst[(q * 5 + i) * 256] = make_uint4(pack_bf16(v[0], v[1]), pack_bf16(v[2], v[3]), pack_bf16(v[4], v[5]), pack_bf16(v[6], v[7]));
        } else {
#pragma unroll
            for (int e = 0; e < 8; e++) own[8 * i + e] = v[e];
        }
    }
    named_bar_sync(1 + wg, 128);
    if ((tid & 127) == 0) flag_signal(&g_flags.p3[tile], 1);
    const int row = m * 128 + wg * 64 + warp * 16 + (lane >> 2);
    const int col = nh * 320 + kq * 80 + (lane & 3) * 2;
    const float bb0 = __bfloat162float(p.b2[row]), bb1 = __bfloat162float(p.b2[row + 8]);
    const uint32_t* x0 = (const uint32_t*)(p.x + (size_t)row * DM + col);
#pragma unroll
    for (int i = 0; i < 10; i++) {
        uint32_t xa = __ldg(x0 + i * 4), xb = __ldg(x0 + 8 * DM / 2 + i * 4);
        own[4 * i + 0] += __uint_as_float(xa << 16) + bb0;
        own[4 * i + 1] += __uint_as_float(xa & 0xffff0000u) + bb0;
        own[4 * i + 2] += __uint_as_float(xb << 16) + bb1;
        own[4 * i + 3] += __uint_as_float(xb & 0xffff0000u) + bb1;
    }
    if ((tid & 127) == 0) flag_wait(&g_flags.p3[tile], 8);
    named_bar_sync(1 + wg, 128);
    uint4 pv[15];
#pragma unroll
    for (int sq = 1; sq < 4; sq++) {
        const uint4* sp = g_part + (size_t)((tile * 4 + ((kq + sq) & 3)) * 4 + kq) * 1280 + tid;
#pragma unroll
        for (int i = 0; i < 5; i++) pv[(sq - 1) * 5 + i] = __ldcg(sp + i * 256);
    }
#pragma unroll
    for (int k = 0; k < 15; k++) {
        const int i = k % 5;
        const uint4 v = pv[k];
        own[8 * i + 0] += __uint_as_float(v.x << 16); own[8 * i + 1] += __uint_as_float(v.x & 0xffff0000u);
        own[8 * i + 2] += __uint_as_float(v.y << 16); own[8 * i + 3] += __uint_as_float(v.y & 0xffff0000u);
        own[8 * i + 4] += __uint_as_float(v.z << 16); own[8 * i + 5] += __uint_as_float(v.z & 0xffff0000u);
        own[8 * i + 6] += __uint_as_float(v.w << 16); own[8 * i + 7] += __uint_as_float(v.w & 0xffff0000u);
    }
    uint32_t* o0 = (uint32_t*)(p.out + (size_t)row * DM + col);
#pragma unroll
    for (int i = 0; i < 10; i++) {
        o0[i * 4] = pack_bf16(own[4 * i], own[4 * i + 1]);
        o0[8 * DM / 2 + i * 4] = pack_bf16(own[4 * i + 2], own[4 * i + 3]);
    }
}

__device__ __forceinline__ int att_row_off(uint32_t rank, int wg) { return rank == 0 ? (wg == 0 ? 0 : 192) : (wg == 0 ? 64 : 128); }

__device__ __forceinline__ void qproj_producer(const Params& p, const Ctx& c, Ring& r, int jb, int hq, int flip) {
    const int R = jb * 256;
    const int r0 = R + att_row_off(c.rank, flip), r1 = R + att_row_off(c.rank, flip ^ 1);
    const int wcol = (hq + 16 * c.rank) * HD;
#pragma unroll 1
    for (int st = 0; st < 20; st++) {
        const uint32_t s = acquire(c, r, 24576);
        const uint32_t bar = (c.sbase + BAR_OFF) + 8 * r.idx;
        tma_load_mc(s + 8192 + c.rank * 8192, &p.wq, wcol, st * 32, bar);
        tma_load_mc(s + 12288 + c.rank * 8192, &p.wq, wcol + 64, st * 32, bar);
        tma_load(s, &p.xn, st * 32, r0, bar);
        tma_load(s + 4096, &p.xn, st * 32, r1, bar);
        r.adv();
    }
}
__device__ __forceinline__ void att_producer(const Params& p, const Ctx& c, Ring& r, int jb, int head, bool check) {
    const int nt = 2 * jb + 2;
    if (check) { flag_wait(&g_flags.kv[head * 8], 64); flag_wait(&g_flags.kv[(32 + head) * 8], 64); }
#pragma unroll 1
    for (int j = 0; j < nt; j++) {
        uint32_t s = acquire(c, r, 32768);
        tma_load_mc(s + c.rank * 16384, &p.kv_ld, c.rank * 64, head * SEQ + j * 128, (c.sbase + BAR_OFF) + 8 * r.idx);
        r.adv();
        s = acquire(c, r, 32768);
        tma_load_mc(s + c.rank * 16384, &p.kv_ld, c.rank * 64, (32 + head) * SEQ + j * 128, (c.sbase + BAR_OFF) + 8 * r.idx);
        r.adv();
    }
}

constexpr float SM_SCALE = 0.08838834764831845f * 1.4426950408889634f;

template<int HALF>
__device__ __forceinline__ void att_qk(uint32_t ks, float (&s)[32], const uint32_t (&q)[32]) {
    wg_fence();
    wgmma_m64n64k16_rs_z<0>(s, q[0], q[1], q[2], q[3], make_desc(ks + HALF * 8192, 16, 1024));
#pragma unroll
    for (int kk = 1; kk < 8; kk++)
        wgmma_m64n64k16_rs<0>(s, q[4 * kk], q[4 * kk + 1], q[4 * kk + 2], q[4 * kk + 3],
                              make_desc(ks + (kk >> 2) * 16384 + HALF * 8192 + (kk & 3) * 32, 16, 1024), 1);
    wg_commit();
}
template<int HALF>
__device__ __forceinline__ void att_pv(uint32_t vs, float (&o)[64], const uint32_t (&pp)[16]) {
    wg_fence();
#pragma unroll
    for (int kk = 0; kk < 4; kk++)
        wgmma_m64n128k16_rs<1>(o, pp[4 * kk], pp[4 * kk + 1], pp[4 * kk + 2], pp[4 * kk + 3],
                               make_desc(vs + (HALF * 4 + kk) * 2048, 16384, 1024), 1);
    wg_commit();
}
template<bool GENERAL>
__device__ __forceinline__ void att_exp_pack(const float (&s)[32], uint32_t (&pp)[16], float (&t)[4], float r0, float r1, int rel) {
#pragma unroll
    for (int j = 0; j < 8; j++) {
        float e0, e1, e2, e3;
        if (GENERAL) {
            e0 = ex2(s[4 * j + 0] - r0); e1 = ex2(s[4 * j + 1] - r0);
            e2 = ex2(s[4 * j + 2] - r1); e3 = ex2(s[4 * j + 3] - r1);
            if (8 * j + 0 > rel)     e0 = 0.f;
            if (8 * j + 1 > rel)     e1 = 0.f;
            if (8 * j + 0 > rel + 8) e2 = 0.f;
            if (8 * j + 1 > rel + 8) e3 = 0.f;
        } else {
            e0 = ex2(s[4 * j + 0]); e1 = ex2(s[4 * j + 1]);
            e2 = ex2(s[4 * j + 2]); e3 = ex2(s[4 * j + 3]);
        }
        if (j == 0) { t[0] = e0; t[1] = e1; t[2] = e2; t[3] = e3; }
        else { t[0] += e0; t[1] += e1; t[2] += e2; t[3] += e3; }
        pp[2 * j] = pack_bf16(e0, e1);
        pp[2 * j + 1] = pack_bf16(e2, e3);
    }
}
__device__ __forceinline__ void att_rowmax(const float (&s)[32], int rel, float& x0, float& x1) {
    x0 = -INFINITY; x1 = -INFINITY;
#pragma unroll
    for (int j = 0; j < 8; j++) {
        x0 = fmaxf(x0, (8 * j + 0 > rel) ? -INFINITY : s[4 * j + 0]);
        x0 = fmaxf(x0, (8 * j + 1 > rel) ? -INFINITY : s[4 * j + 1]);
        x1 = fmaxf(x1, (8 * j + 0 > rel + 8) ? -INFINITY : s[4 * j + 2]);
        x1 = fmaxf(x1, (8 * j + 1 > rel + 8) ? -INFINITY : s[4 * j + 3]);
    }
    x0 = fmaxf(x0, __shfl_xor_sync(0xffffffffu, x0, 1));
    x1 = fmaxf(x1, __shfl_xor_sync(0xffffffffu, x1, 1));
    x0 = fmaxf(x0, __shfl_xor_sync(0xffffffffu, x0, 2));
    x1 = fmaxf(x1, __shfl_xor_sync(0xffffffffu, x1, 2));
}
__device__ __forceinline__ int att_rel(bool mask) {
    const int lane = threadIdx.x & 31;
    return mask ? (int)(((threadIdx.x >> 5) & 3) * 16 + (lane >> 2) - 2 * (lane & 3)) : 4096;
}
__device__ __forceinline__ void att_softmax(const float (&s)[32], bool mask, uint32_t (&pp)[16], float (&o)[64], float (&ls)[4], float (&t)[4],
                                            float& r0, float& r1, bool& useref, int dbg) {
    const int rel = att_rel(mask);
    if (__builtin_expect(useref && !mask, 0)) att_exp_pack<true>(s, pp, t, r0, r1, rel);
    bool bad = !((t[0] + t[1]) + (t[2] + t[3]) < 1.2379400392853803e27f);
    if (__builtin_expect(__any_sync(0xffffffffu, bad), 0)) {
        wg_wait<0>(); fence_regs(o);
        float x0, x1;
        att_rowmax(s, rel, x0, x1);
        const float n0 = fmaxf(r0, x0), n1 = fmaxf(r1, x1);
        const float a0 = ex2(r0 - n0), a1 = ex2(r1 - n1);
        r0 = n0; r1 = n1;
        useref = true;
        ls[0] *= a0; ls[1] *= a0; ls[2] *= a1; ls[3] *= a1;
#pragma unroll
        for (int i = 0; i < 16; i++) {
            o[4 * i + 0] *= a0; o[4 * i + 1] *= a0;
            o[4 * i + 2] *= a1; o[4 * i + 3] *= a1;
        }
        att_exp_pack<true>(s, pp, t, r0, r1, rel);
    }
    ls[0] += t[0]; ls[1] += t[1]; ls[2] += t[2]; ls[3] += t[3];
}

__device__ __forceinline__ void att_load_q(uint32_t (&q)[32], const uint4* src) {
#pragma unroll
    for (int i = 0; i < 8; i++) {
        uint4 v = src[i * 128];
        q[4 * i] = v.x; q[4 * i + 1] = v.y; q[4 * i + 2] = v.z; q[4 * i + 3] = v.w;
    }
}
__device__ __forceinline__ void att_head(const Params& p, const Ctx& c, Ring& r, uint32_t (&q)[32], const uint4* qnext, int nt_cta, int row_base  ,
                                         int head, float (&o)[64], float& inv0, float& inv1) {
    const int nh = (row_base >> 6) + 1;
    Ring kc = r, vc = r; vc.adv();
    float sa[32], sb[32];
    uint32_t pa[16], pb[16];
    float ls[4] = {0.f, 0.f, 0.f, 0.f};
    float t[4];
    float r0 = 0.f, r1 = 0.f;
    int vpend = -1;
#pragma unroll
    for (int i = 0; i < 64; i++) o[i] = 0.f;
#pragma unroll
    for (int i = 0; i < 16; i++) { pa[i] = 0u; pb[i] = 0u; }
    wait_full(c, kc);
    att_qk<0>(slot_addr(c, kc.idx), sa, q);
    wg_wait<0>(); fence_regs(sa);
    if (nh == 1) { release(c, kc.idx); kc.adv2(); }
    att_rowmax(sa, att_rel(nh == 1), r0, r1);
    if (r0 >= -40.f && r0 <= 80.f) r0 = 0.f;
    if (r1 >= -40.f && r1 <= 80.f) r1 = 0.f;
    bool useref = __any_sync(0xffffffffu, r0 != 0.f || r1 != 0.f);
    for (int h = 0;; h += 2) {
        const bool moreB = h + 1 < nh;
        if (moreB) {
            att_qk<1>(slot_addr(c, kc.idx), sb, q);
            att_exp_pack<false>(sa, pa, t, r0, r1, 0);
        } else {
            if (qnext) att_load_q(q, qnext);
            att_exp_pack<true>(sa, pa, t, r0, r1, att_rel(true));
        }
        att_softmax(sa, !moreB, pa, o, ls, t, r0, r1, useref, h);
        wait_full(c, vc);
        att_pv<0>(slot_addr(c, vc.idx), o, pa);
        if (!moreB) {
            wg_wait<0>(); fence_regs(o);
            if (vpend >= 0) release(c, vpend);
            release(c, vc.idx); vc.adv2();
            break;
        }
        wg_wait<1>(); fence_regs(sb); fence_regs_u(pb);
        if (vpend >= 0) release(c, vpend);
        release(c, kc.idx); kc.adv2();
        const bool moreA = h + 2 < nh;
        if (moreA) {
            wait_full(c, kc);
            att_qk<0>(slot_addr(c, kc.idx), sa, q);
            att_exp_pack<false>(sb, pb, t, r0, r1, 0);
        } else {
            if (qnext) att_load_q(q, qnext);
            att_exp_pack<true>(sb, pb, t, r0, r1, att_rel(true));
        }
        att_softmax(sb, !moreA, pb, o, ls, t, r0, r1, useref, h + 1);
        att_pv<1>(slot_addr(c, vc.idx), o, pb);
        vpend = vc.idx; vc.adv2();
        if (!moreA) {
            wg_wait<0>(); fence_regs(o);
            release(c, vpend);
            break;
        }
        wg_wait<1>(); fence_regs(sa); fence_regs_u(pa);
        if (h + 3 == nh) { release(c, kc.idx); kc.adv2(); }
    }
    for (int j = (nh + 1) >> 1; j < nt_cta; j++) {
        wait_full(c, kc); release(c, kc.idx); kc.adv2();
        wait_full(c, vc); release(c, vc.idx); vc.adv2();
    }
    r = kc;
    ls[0] += ls[1]; ls[2] += ls[3];
    ls[0] += __shfl_xor_sync(0xffffffffu, ls[0], 1);
    ls[2] += __shfl_xor_sync(0xffffffffu, ls[2], 1);
    ls[0] += __shfl_xor_sync(0xffffffffu, ls[0], 2);
    ls[2] += __shfl_xor_sync(0xffffffffu, ls[2], 2);
    inv0 = __fdividef(1.0f, ls[0]);
    inv1 = __fdividef(1.0f, ls[2]);
}

__device__ __forceinline__ void att_store(const Params& p, Ctx& c, const float (&o)[64], float inv0, float inv1, int row_base, int head) {
    const int tid = threadIdx.x, wg = c.wg, warp = (tid >> 5) & 3, lane = tid & 31;
    uint32_t stg = c.sbase + STG_OFF + wg * 16384;
    const int mi = lane >> 3;
    const int row = warp * 16 + (lane & 7) + 8 * (mi & 1);
#pragma unroll
    for (int jj = 0; jj < 8; jj++) {
        int chunk = 2 * (jj & 3) + (mi >> 1);
        stmatrix_x4(stg + (jj >> 2) * 8192 + row * 128 + ((chunk ^ (row & 7)) << 4),
                    pack_bf16(o[8 * jj + 0] * inv0, o[8 * jj + 1] * inv0), pack_bf16(o[8 * jj + 2] * inv1, o[8 * jj + 3] * inv1),
                    pack_bf16(o[8 * jj + 4] * inv0, o[8 * jj + 5] * inv0), pack_bf16(o[8 * jj + 6] * inv1, o[8 * jj + 7] * inv1));
    }
    stage_submit(c, &p.ctx_st, head * HD, row_base, stg, 2, &g_flags.ctx[(row_base >> 8) * 32 + head]);
}

__device__ __forceinline__ void qproj_consumer(Ctx& c, Ring& r, uint32_t (&q)[32], uint4* stash) {
    const int wg = c.wg;
    float qa[128];
#pragma unroll
    for (int i = 0; i < 128; i++) qa[i] = 0.f;
    uint32_t prev = 0;
#pragma unroll 1
    for (int st = 0; st < 20; st++) {
        wait_full(c, r);
        const uint32_t sl = slot_addr(c, r.idx);
        wg_fence();
#pragma unroll
        for (int kk = 0; kk < 2; kk++)
            wgmma_m64n256k16_ss<0, 1>(qa, (make_desc(sl + wg * 4096 + kk * 32, 16, 512) & ~(3ull << 62)) | (2ull << 62),
                                      make_desc(sl + 8192 + kk * 2048, 4096, 1024), 1);
        wg_commit();
        if (st > 0) { wg_wait<1>(); release(c, prev); }
        prev = r.idx;
        r.adv();
    }
    wg_wait<0>(); fence_regs(qa);
    release(c, prev);
#pragma unroll
    for (int i = 0; i < 32; i++) q[i] = pack_bf16(qa[2 * i] * SM_SCALE, qa[2 * i + 1] * SM_SCALE);
#pragma unroll
    for (int i = 0; i < 8; i++)
        stash[i * 128] = make_uint4(pack_bf16(qa[64 + 8 * i + 0] * SM_SCALE, qa[64 + 8 * i + 1] * SM_SCALE), pack_bf16(qa[64 + 8 * i + 2] * SM_SCALE, qa[64 + 8 * i + 3] * SM_SCALE),
                                    pack_bf16(qa[64 + 8 * i + 4] * SM_SCALE, qa[64 + 8 * i + 5] * SM_SCALE), pack_bf16(qa[64 + 8 * i + 6] * SM_SCALE, qa[64 + 8 * i + 7] * SM_SCALE));
}

__device__ __forceinline__ void att_consumer(const Params& p, Ctx& c, Ring& r, int j, int hq) {
    const int tid = threadIdx.x, wg = c.wg;
    uint32_t q[32];
    float o[64];
    float inv0, inv1;
#pragma unroll 1
    for (int step = 0; step < 4; step++) {
        const int jb = (step & 1) ? j : 7 - j;
        const int grp = step >> 1;
        const int rwg = wg ^ grp ^ (step & 1);
        const int row_base = jb * 256 + att_row_off(c.rank, rwg);
        uint4* stash = g_qstash + (size_t)((blockIdx.x * 2 + (step & 1)) * 2 + rwg) * 1024 + (tid & 127);
        if (grp == 0) {
            qproj_consumer(c, r, q, stash);
            if (step == 1) { __threadfence_block(); named_bar_sync(3, 256); }
        }
        const uint4* qnext = nullptr;
        if (step == 1 || step == 2) {
            const int ns = step + 1;
            qnext = g_qstash + (size_t)((blockIdx.x * 2 + (ns & 1)) * 2 + (wg ^ 1 ^ (ns & 1))) * 1024 + (tid & 127);
        }
        att_head(p, c, r, q, qnext, 2 * jb + 2, row_base, hq + 16 * grp, o, inv0, inv1);
        stage_acquire(c, true);
        att_store(p, c, o, inv0, inv1, row_base, hq + 16 * grp);
    }
}

__device__ __forceinline__ float warp_sum(float v) {
#pragma unroll
    for (int o = 16; o > 0; o >>= 1) v += __shfl_xor_sync(0xffffffffu, v, o);
    return v;
}
__device__ __forceinline__ void ln_row(float (&v)[20]) {
    float s = 0.f;
#pragma unroll
    for (int i = 0; i < 20; i++) s += v[i];
    float mean = warp_sum(s) * (1.0f / DM);
    float q = 0.f;
#pragma unroll
    for (int i = 0; i < 20; i++) { float d = v[i] - mean; q = fmaf(d, d, q); }
    float var = bf16r(warp_sum(q) * (1.0f / DM));
    float mb = bf16r(mean);
    float rden = __fdiv_rn(1.0f, bf16r(sqrtf(bf16r(var + 1e-5f))));
#pragma unroll
    for (int i = 0; i < 20; i++) v[i] = bf16r(bf16r(v[i] - mb) * rden);
}
__device__ __forceinline__ void ln_job(const Params& p, const Ctx& c, const uint2 (&xr)[2][5]) {
    const int lane = threadIdx.x & 31;
    const int row0 = blockIdx.x * 16 + (threadIdx.x >> 5) * 2;
    float v[2][20];
#pragma unroll
    for (int k = 0; k < 2; k++)
#pragma unroll
        for (int i = 0; i < 5; i++) {
            uint2 u = xr[k][i];
            v[k][4 * i + 0] = __uint_as_float(u.x << 16); v[k][4 * i + 1] = __uint_as_float(u.x & 0xffff0000u);
            v[k][4 * i + 2] = __uint_as_float(u.y << 16); v[k][4 * i + 3] = __uint_as_float(u.y & 0xffff0000u);
        }
#pragma unroll 1
    for (int pass = 0; pass < 2; pass++) {
        bf16* dst = pass == 0 ? g_xn : g_h;
#pragma unroll
        for (int k = 0; k < 2; k++) {
            ln_row(v[k]);
            uint2* o = (uint2*)(dst + (size_t)(row0 + k) * DM);
#pragma unroll
            for (int i = 0; i < 5; i++) o[lane + 32 * i] = make_uint2(pack_bf16(v[k][4 * i], v[k][4 * i + 1]), pack_bf16(v[k][4 * i + 2], v[k][4 * i + 3]));
        }
    }
    __syncwarp();
    mbar_arrive_if((c.sbase + BAR_OFF) + 192, lane == 0);
}

__device__ __forceinline__ void kv_range(int sub, int& t0, int& t1) {
    t0 = sub * 18 + (sub < 2 ? sub : 2);
    t1 = t0 + (sub < 2 ? 19 : 18);
}

__global__ void __cluster_dims__(2, 1, 1) __launch_bounds__(NTHREADS, 1) main_kernel(const __grid_constant__ Params p) {
    extern __shared__ __align__(1024) uint8_t smem_raw[];
    const int tid = threadIdx.x;
    uint2 xr[2][5];
    if (tid < 256 && blockIdx.x < 128) {
        const uint2* xp = (const uint2*)(p.x + (size_t)(blockIdx.x * 16 + (tid >> 5) * 2) * DM) + (tid & 31);
#pragma unroll
        for (int k = 0; k < 2; k++)
#pragma unroll
            for (int i = 0; i < 5; i++) xr[k][i] = __ldg(xp + k * (DM / 4) + 32 * i);
    }
    if (tid == 256) { prefetch_tmap(&p.ckv); prefetch_tmap(&p.wuk); prefetch_tmap(&p.wuv); prefetch_tmap(&p.w1); prefetch_tmap(&p.h); }
    if (tid == 288) { prefetch_tmap(&p.kv_st); prefetch_tmap(&p.xn); prefetch_tmap(&p.wq); prefetch_tmap(&p.kv_ld); }
    Ctx c;
    c.sbase = (smem_u32(smem_raw) + 1023) & ~1023u;
    c.rank = cluster_rank();
    c.empty_rel = mapa_u32((c.sbase + BAR_OFF + 64), (threadIdx.x & 1) ? (c.rank ^ 1) : c.rank);
    c.sk = 0;
    c.wg = __shfl_sync(0xffffffffu, tid >> 7, 0);
    if (tid == 256) {
        for (int i = 0; i < NSLOT; i++) { mbar_init((c.sbase + BAR_OFF) + 8 * i, 1); mbar_init((c.sbase + BAR_OFF + 64) + 8 * i, 16); }
        for (int i = 0; i < 4; i++) { mbar_init((c.sbase + BAR_OFF) + 128 + 8 * i, 4); mbar_init((c.sbase + BAR_OFF) + 160 + 8 * i, 1); }
        mbar_init((c.sbase + BAR_OFF) + 192, 8);
        asm volatile("fence.mbarrier_init.release.cluster;" ::: "memory");
    }
    cluster_sync_all();
    const int cid = blockIdx.x >> 1;
    Ring r; r.idx = 0; r.phase = 0;

    if (c.wg == 2) {
        reg_dealloc<24>();
        if (tid == 256) {
            if (cid < 64 && (cid & 7) < 7) {
                int t0, t1; kv_range(cid & 7, t0, t1);
                kv_producer(p, c, r, (cid >> 3) * 2 + c.rank, t0, t1);
                flag_wait(&g_flags.ln, 128);
            } else {
                const int id0 = cid < 64 ? (cid >> 3) : 8 + (cid - 64) * 3;
                const int n1 = cid < 64 ? 1 : 3;
                flag_wait(&g_flags.ln, 128);
#pragma unroll 1
                for (int i = 0; i < n1; i++) {
                    b1_producer(p, c, r, ((id0 + i) >> 1) * 2 + c.rank, (id0 + i) & 1);
                }
            }
            if (cid < 64) {
                const int hq = cid & 15, j = cid >> 4;
#pragma unroll 1
                for (int step = 0; step < 4; step++) {
                    const int jb = (step & 1) ? j : 7 - j;
                    if (step < 2) qproj_producer(p, c, r, jb, hq, step & 1);
                    att_producer(p, c, r, jb, hq + 16 * (step >> 1), (step & 1) == 0);
                }
                p3_producer(p, c, r, (cid >> 3) * 2 + c.rank, (cid >> 2) & 1, cid & 3);
            }
        } else if (tid == 288) {
            store_agent(c, 0);
        } else if (tid == 320) {
            store_agent(c, 1);
        } else if (tid == 352) {
            if (cid < 64) {
                mbar_wait((c.sbase + BAR_OFF) + 192, 0);
                flag_signal(&g_flags.ln, 1);
            }
        }
        __syncwarp();
        cluster_sync_all();
    } else {
        reg_alloc<240>();
        if (cid < 64) ln_job(p, c, xr);
        if (cid < 64 && (cid & 7) < 7) {
            int t0, t1; kv_range(cid & 7, t0, t1);
            kv_consumer(p, c, r, (cid >> 3) * 2 + c.rank, t0, t1);
        } else {
            const int id0 = cid < 64 ? (cid >> 3) : 8 + (cid - 64) * 3;
            const int n1 = cid < 64 ? 1 : 3;
#pragma unroll 1
            for (int i = 0; i < n1; i++) {
                b1_consumer(p, c, r, ((id0 + i) >> 1) * 2 + c.rank, (id0 + i) & 1);
            }
        }
        if (cid < 64) {
            att_consumer(p, c, r, cid >> 4, cid & 15);
            p3_consumer(p, c, r, (cid >> 3) * 2 + c.rank, (cid >> 2) & 1, cid & 3);
        }
        stage_acquire(c, false);
        stage_submit(c, nullptr, 0, 0, 0, 0, nullptr);
        cluster_sync_all();
        if (tid < 32) {
            uint32_t ticket = 0;
            if (tid == 0) ticket = atomicAdd(&g_flags.done, 1u);
            ticket = __shfl_sync(0xffffffffu, ticket, 0);
            if (ticket == gridDim.x - 1) {
                uint4* f = (uint4*)&g_flags;
                for (int i = tid; i < (int)(sizeof(Flags) / 16); i += 32) f[i] = make_uint4(0, 0, 0, 0);
                if (tid == 0) g_abort = 0;
            }
        }
    }
}

typedef CUresult (*PFN_encodeTiled)(CUtensorMap*, CUtensorMapDataType, cuuint32_t, void*, const cuuint64_t*, const cuuint64_t*,
                                    const cuuint32_t*, const cuuint32_t*, CUtensorMapInterleave, CUtensorMapSwizzle,
                                    CUtensorMapL2promotion, CUtensorMapFloatOOBfill);

static void make_map(PFN_encodeTiled enc, CUtensorMap* m, const void* ptr, uint64_t rows, uint64_t cols, uint32_t box_rows, uint32_t box_cols = 64) {
    cuuint64_t dims[2] = {cols, rows};
    cuuint64_t strides[1] = {cols * 2};
    cuuint32_t box[2] = {box_cols, box_rows};
    cuuint32_t es[2] = {1, 1};
    enc(m, CU_TENSOR_MAP_DATA_TYPE_BFLOAT16, 2, (void*)ptr, dims, strides, box, es, CU_TENSOR_MAP_INTERLEAVE_NONE,
        box_cols == 64 ? CU_TENSOR_MAP_SWIZZLE_128B : CU_TENSOR_MAP_SWIZZLE_64B, CU_TENSOR_MAP_L2_PROMOTION_L2_128B,
        CU_TENSOR_MAP_FLOAT_OOB_FILL_NONE);
}

extern "C" void kernel_launch(void* const* d_in, const int* in_sizes, int n_in, void* d_out, int out_size) {
    const bf16* x   = (const bf16*)d_in[0];
    const bf16* ckv = (const bf16*)d_in[1];
    const bf16* wq  = (const bf16*)d_in[2];
    const bf16* wuk = (const bf16*)d_in[3];
    const bf16* wuv = (const bf16*)d_in[4];
    const bf16* wo  = (const bf16*)d_in[5];
    const bf16* w1  = (const bf16*)d_in[7];
    const bf16* b1  = (const bf16*)d_in[8];
    const bf16* w2  = (const bf16*)d_in[9];
    const bf16* b2  = (const bf16*)d_in[10];

    static PFN_encodeTiled enc = nullptr;
    static void *p_xn, *p_h, *p_kv, *p_ctx, *p_uT;
    if (!enc) {
        void* fn = nullptr;
        cudaDriverEntryPointQueryResult st;
        cudaGetDriverEntryPoint("cuTensorMapEncodeTiled", &fn, cudaEnableDefault, &st);
        enc = (PFN_encodeTiled)fn;
        cudaGetSymbolAddress(&p_xn, g_xn);
        cudaGetSymbolAddress(&p_h, g_h);
        cudaGetSymbolAddress(&p_kv, g_kv);
        cudaGetSymbolAddress(&p_ctx, g_ctx);
        cudaGetSymbolAddress(&p_uT, g_uT);
        cudaFuncSetAttribute(main_kernel, cudaFuncAttributeMaxDynamicSharedMemorySize, SMEM_BYTES);
    }
    Params p;
    make_map(enc, &p.ckv, ckv, SEQ, DC, 128);
    make_map(enc, &p.wuk, wuk, DC, NH * HD, 128);
    make_map(enc, &p.wuv, wuv, DC, NH * HD, 128);
    make_map(enc, &p.kv_st, p_kv, 64 * SEQ, HD, 64);
    make_map(enc, &p.kv_ld, p_kv, 64 * SEQ, HD, 128);
    make_map(enc, &p.xn, p_xn, SEQ, DM, 64, 32);
    make_map(enc, &p.wq, wq, DM, NH * HD, 32);
    make_map(enc, &p.ctx_st, p_ctx, SEQ, NH * HD, 64);
    make_map(enc, &p.ctx_ld, p_ctx, SEQ, NH * HD, 128, 32);
    make_map(enc, &p.wo, wo, NH * HD, DM, 32);
    make_map(enc, &p.w2, w2, FF, SEQ, 32);
    make_map(enc, &p.uT, p_uT, FF, DM, 32);
    make_map(enc, &p.uT_st, p_uT, FF, DM, 64);
    make_map(enc, &p.w1, w1, SEQ, FF, 32);
    make_map(enc, &p.h, p_h, SEQ, DM, 32);
    p.b1 = b1; p.b2 = b2; p.x = x;
    p.out = (bf16*)d_out;

    main_kernel<<<132, NTHREADS, SMEM_BYTES, cudaStreamPerThread>>>(p);
}
```
